```python
import torch

def _softmax(x, axis=-1):
    return torch.softmax(x, dim=axis)
def _gelu(x):
    return torch.nn.functional.gelu(x, approximate="tanh")
def _silu(x):
    return torch.nn.functional.silu(x)
def _sigmoid(x):
    return torch.sigmoid(x)
def _layernorm(x, axis=-1, eps=1e-5):
    m = x.mean(dim=axis, keepdim=True)
    v = x.var(dim=axis, keepdim=True, unbiased=False)
    return (x - m) / torch.sqrt(v + eps)
def _scatter_add(tgt, idx, src, axis=0):
    return tgt.clone().index_add_(axis, idx, src)
def _segment_sum(src, seg, n):
    out = torch.zeros((n,) + src.shape[1:], dtype=src.dtype)
    return out.index_add_(0, seg, src)
def _pad(x, pw):
    flat = tuple(v for pair in reversed(pw) for v in pair)
    return torch.nn.functional.pad(x, flat)

kernel_name = 'standalone__sliding_block_cached__decode'

def setup_inputs():

    _w = (lambda a: (lambda t: t.to(torch.bfloat16) if t.is_floating_point() else t)(torch.as_tensor(a)))
    B, Sq, D = 4, 1, 448
    Hq, Hkv, Sk, Dh = 16, 8, 4096, 256
    assert Hq % Hkv == 0, (Hq, Hkv)
    return {
        "x": _w((lambda *s: torch.randn(*s, dtype=torch.bfloat16) * 0.8)(B, Sq, D)),
        "k_cache": _w((lambda *s: torch.randn(*s, dtype=torch.bfloat16) * 0.8)(B, Hkv, Sk, Dh)),
        "v_cache": _w((lambda *s: torch.randn(*s, dtype=torch.bfloat16) * 0.05)(B, Hkv, Sk, Dh)),
        "wq": _w((lambda *s: torch.randn(*s, dtype=torch.bfloat16) * 0.8)(D, Hq * Dh) * (D ** -0.5)),
        "wo": _w((lambda *s: torch.randn(*s, dtype=torch.bfloat16) * 0.05)(Hq * Dh, D) * ((Hq * Dh) ** -0.5)),
    }

def reference(x, k_cache, v_cache, wq, wo):
    B, Sq, D = x.shape
    Hq, Dh = 16, 256
    Hkv, Sk = k_cache.shape[1], k_cache.shape[2]
    W = min(4096, max(256, Sk // 4))
    rep = Hq // Hkv
    q = (lambda x, *d: x.permute(*d))((x @ wq).reshape(B, Sq, Hq, Dh), 0, 2, 1, 3)
    k = (lambda x, n, axis: torch.repeat_interleave(x, n, dim=axis))(k_cache[:, :, Sk - W:, :], rep, axis=1)
    v = (lambda x, n, axis: torch.repeat_interleave(x, n, dim=axis))(v_cache[:, :, Sk - W:, :], rep, axis=1)
    scores = torch.einsum("bhqd,bhkd->bhqk", q, k) * (Dh ** -0.5)
    p = _softmax(scores, axis=-1)
    o = torch.einsum("bhqk,bhkd->bhqd", p, v)
    return (lambda x, *d: x.permute(*d))(o, 0, 2, 1, 3).reshape(B, Sq, Hq * Dh) @ wo
```

```cpp
#include <cuda_runtime.h>
#include <cuda_bf16.h>
#include <cuda.h>
#include <stdint.h>

namespace {

constexpr int SK = 4096, WIN0 = 3072;
constexpr int SLOT = 16384;
constexpr int NSLOT = 6;
constexpr int OFF_BAR  = NSLOT * SLOT;
constexpr int OFF_QBUF = OFF_BAR + 416;
constexpr int OFF_QS   = OFF_QBUF + 4096;
constexpr int OFF_WST  = OFF_QS + 1024;
constexpr int OFF_OB   = OFF_WST + 192;
constexpr int OFF_HOP  = OFF_OB + 2048;
constexpr int OFF_QRED = OFF_HOP + 2048;
constexpr int OFF_PS   = OFF_QRED;
constexpr int OFF_PROF = OFF_QRED + 7 * 1024;
constexpr int SMEM_BYTES = OFF_PROF;
static_assert(SMEM_BYTES <= 115712, "two CTAs must fit on one SM");
constexpr int NTHREADS = 288;
constexpr int SPIN_LIMIT = 1 << 20;

#define WINK 8
#define WINV 8
#define COUNTWIN 0
#define PSLEEP 50
#define CSLEEP 50
#define K0FIRST 0
#define WARM 0
#define SKEL 0
#define CLDIM 16
#define WINV7 12
#define NOST 0
#define OMAP 1
#define PF 2
#define PFN 64
#define UNB 1
#define NPACED 4
#define NORD 16
#define PACE0 1000
#define PACE 1300
#define VPROMO 0
#define ST_TRIG 8

#define AG 16
#define AS 32
#define ACC_IDX(c, j) ((((c) * 256 + (j)) / AG) * AS + (j) % AG)
constexpr int ACC_WORDS = 1792 / AG * AS;
__device__ __align__(1024) unsigned long long g_acc[ACC_WORDS];
__device__ float g_side[ACC_WORDS];

#define SKEL_EXIT() do { if (SKEL) return; } while (0)
#define TS(i)
#define TC(i)
#define TC_DUMP()
#define TP(i)
#define PROF_DUMP()

__device__ __forceinline__ void mbar_init(uint32_t bar, uint32_t cnt) {
    asm volatile("mbarrier.init.shared::cta.b64 [%0], %1;" ::"r"(bar), "r"(cnt) : "memory");
}
__device__ __forceinline__ void mbar_expect_tx(uint32_t bar, uint32_t bytes) {
    asm volatile("mbarrier.arrive.expect_tx.shared::cta.b64 _, [%0], %1;" ::"r"(bar), "r"(bytes) : "memory");
}
__device__ __forceinline__ void mbar_arrive(uint32_t bar) {
    asm volatile("mbarrier.arrive.shared::cta.b64 _, [%0];" ::"r"(bar) : "memory");
}
__device__ __forceinline__ void mbar_wait_n(uint32_t bar, uint32_t& n) {
    asm volatile("{\n.reg .pred p, q;\n"
                 "WAIT_LOOP:\n"
                 "mbarrier.try_wait.parity.shared::cta.b64 p, [%1], 0;\n"
                 "add.u32 %0, %0, 1;\n"
                 "setp.lt.and.u32 q, %0, %2, !p;\n"
                 "@q bra.uni WAIT_LOOP;\n}"
                 : "+r"(n) : "r"(bar), "n"(SPIN_LIMIT) : "memory");
}
__device__ __forceinline__ void mbar_wait_u(uint32_t bar) {
    asm volatile("{\n.reg .pred p;\nWAIT_LOOP:\nmbarrier.try_wait.parity.shared::cta.b64 p, [%0], 0;\n@!p bra.uni WAIT_LOOP;\n}" ::"r"(bar) : "memory");
}
#define mbar_wait(bar) mbar_wait_n(bar, spins)
#define mbar_wait_t(bar) mbar_wait_u(bar)
__device__ __forceinline__ bool mbar_try(uint32_t bar) {
    uint32_t ok;
    asm volatile("{\n.reg .pred p;\nmbarrier.try_wait.parity.shared::cta.b64 p, [%1], 0;\nselp.u32 %0, 1, 0, p;\n}"
                 : "=r"(ok) : "r"(bar) : "memory");
    return ok != 0;
}
__device__ __forceinline__ void bulk_g2s(uint32_t dst, const void* src, uint32_t bytes, uint32_t bar) {
    asm volatile("cp.async.bulk.shared::cluster.global.mbarrier::complete_tx::bytes [%0], [%1], %2, [%3];"
                 ::"r"(dst), "l"(src), "r"(bytes), "r"(bar) : "memory");
}
__device__ __forceinline__ void tma2d(uint32_t dst, const CUtensorMap* tm, int c0, int c1, uint32_t bar) {
    asm volatile("cp.async.bulk.tensor.2d.shared::cluster.global.mbarrier::complete_tx::bytes [%0], [%1, {%3, %4}], [%2];"
                 ::"r"(dst), "l"(tm), "r"(bar), "r"(c0), "r"(c1) : "memory");
}
__device__ __forceinline__ void tma3d(uint32_t dst, const CUtensorMap* tm, int c1, uint32_t bar) {
    asm volatile("cp.async.bulk.tensor.3d.shared::cluster.global.mbarrier::complete_tx::bytes [%0], [%1, {%3, %4, %3}], [%2];"
                 ::"r"(dst), "l"(tm), "r"(bar), "r"(0), "r"(c1) : "memory");
}
__device__ __forceinline__ uint32_t pin(uint32_t v) {
    uint32_t o;
    asm volatile("shfl.sync.bfly.b32 %0, %1, 0, 0x1f, 0xffffffff;" : "=r"(o) : "r"(v));
    return o;
}
template <typename T> __device__ __forceinline__ T* pin_ptr(T* p) {
    const unsigned long long a = (unsigned long long)p;
    return (T*)(((unsigned long long)pin((uint32_t)(a >> 32)) << 32) | pin((uint32_t)a));
}
__device__ __forceinline__ bool elect_one() {
    uint32_t p;
    asm volatile("{\n.reg .pred P;\nelect.sync _|P, 0xffffffff;\nselp.u32 %0, 1, 0, P;\n}" : "=r"(p));
    return p != 0;
}
__device__ __forceinline__ void bar_sync(int id, int n) { asm volatile("bar.sync %0, %1;" ::"r"(id), "r"(n) : "memory"); }
__device__ __forceinline__ void cluster_arrive() { asm volatile("barrier.cluster.arrive.relaxed.aligned;" ::: "memory"); }
__device__ __forceinline__ void cluster_wait() { asm volatile("barrier.cluster.wait.aligned;" ::: "memory"); }
__device__ __forceinline__ void fence_mbar_init() { asm volatile("fence.mbarrier_init.release.cluster;" ::: "memory"); }
__device__ __forceinline__ uint32_t mapa(uint32_t a, uint32_t rank) {
    uint32_t o;
    asm("mapa.shared::cluster.u32 %0, %1, %2;" : "=r"(o) : "r"(a), "r"(rank));
    return o;
}
__device__ __forceinline__ void st_async128(uint32_t a, uint32_t x, uint32_t y, uint32_t z, uint32_t w, uint32_t bar) {
    asm volatile("st.async.shared::cluster.mbarrier::complete_tx::bytes.v4.b32 [%0], {%1,%2,%3,%4}, [%5];"
                 ::"r"(a), "r"(x), "r"(y), "r"(z), "r"(w), "r"(bar) : "memory");
}
__device__ __forceinline__ void st_async64(uint32_t a, uint32_t x, uint32_t y, uint32_t bar) {
    asm volatile("st.async.shared::cluster.mbarrier::complete_tx::bytes.v2.b32 [%0], {%1,%2}, [%3];"
                 ::"r"(a), "r"(x), "r"(y), "r"(bar) : "memory");
}

__device__ __forceinline__ uint32_t prmt(uint32_t a, uint32_t sel) {
    uint32_t o;
    asm("prmt.b32 %0, %1, 0, %2;" : "=r"(o) : "r"(a), "r"(sel));
    return o;
}
__device__ __forceinline__ float acc_value(unsigned long long tot) {
    return fmaf((float)(int)(uint32_t)(tot >> 32), 0x1p-24f, (float)((uint32_t)tot >> 10) * 0x1p-46f);
}
__device__ __noinline__ void finish_with_side(unsigned long long tot, unsigned long long* acc_p, __nv_bfloat16* out_p) {
    if ((tot & 31ull) != 16ull) return;
    __threadfence();
    const float side = atomicExch(&g_side[acc_p - g_acc], 0.0f);
    *out_p = __float2bfloat16(acc_value(tot) + side);
    *acc_p = 0ull;
}
__device__ __noinline__ void accumulate_slow(float sum, unsigned long long* acc_p, __nv_bfloat16* out_p) {
    atomicAdd(&g_side[acc_p - g_acc], sum);
    __threadfence();
    finish_with_side(atomicAdd(acc_p, 33ull) + 33ull, acc_p, out_p);
}

__device__ __forceinline__ void mma16816(float (&c)[4], uint32_t a0, uint32_t a1, uint32_t a2, uint32_t a3,
                                         uint32_t b0, uint32_t b1) {
    asm volatile("mma.sync.aligned.m16n8k16.row.col.f32.bf16.bf16.f32 {%0,%1,%2,%3}, {%4,%5,%6,%7}, {%8,%9}, {%0,%1,%2,%3};"
                 : "+f"(c[0]), "+f"(c[1]), "+f"(c[2]), "+f"(c[3])
                 : "r"(a0), "r"(a1), "r"(a2), "r"(a3), "r"(b0), "r"(b1));
}
__device__ __forceinline__ uint4 lds128(uint32_t a) {
    uint4 v;
    asm volatile("ld.shared.v4.u32 {%0,%1,%2,%3}, [%4];" : "=r"(v.x), "=r"(v.y), "=r"(v.z), "=r"(v.w) : "r"(a) : "memory");
    return v;
}
__device__ __forceinline__ float4 lds128f(uint32_t a) {
    float4 v;
    asm volatile("ld.shared.v4.f32 {%0,%1,%2,%3}, [%4];" : "=f"(v.x), "=f"(v.y), "=f"(v.z), "=f"(v.w) : "r"(a) : "memory");
    return v;
}
__device__ __forceinline__ float2 lds64f(uint32_t a) {
    float2 v;
    asm volatile("ld.shared.v2.f32 {%0,%1}, [%2];" : "=f"(v.x), "=f"(v.y) : "r"(a) : "memory");
    return v;
}
__device__ __forceinline__ uint2 lds64(uint32_t a) {
    uint2 v;
    asm volatile("ld.shared.v2.u32 {%0,%1}, [%2];" : "=r"(v.x), "=r"(v.y) : "r"(a) : "memory");
    return v;
}
__device__ __forceinline__ float lds32f(uint32_t a) {
    float v;
    asm volatile("ld.shared.f32 %0, [%1];" : "=f"(v) : "r"(a) : "memory");
    return v;
}
__device__ __forceinline__ void sts128f(uint32_t a, float x, float y, float z, float w) {
    asm volatile("st.shared.v4.f32 [%0], {%1,%2,%3,%4};" ::"r"(a), "f"(x), "f"(y), "f"(z), "f"(w) : "memory");
}
__device__ __forceinline__ void sts32(uint32_t a, uint32_t v) {
    asm volatile("st.shared.u32 [%0], %1;" ::"r"(a), "r"(v) : "memory");
}
__device__ __forceinline__ void sts16(uint32_t a, unsigned short v) {
    asm volatile("st.shared.u16 [%0], %1;" ::"r"(a), "h"(v) : "memory");
}
__device__ __forceinline__ uint4 ldsm4t(uint32_t a) {
    uint4 v;
    asm volatile("ldmatrix.sync.aligned.m8n8.x4.trans.shared.b16 {%0,%1,%2,%3}, [%4];"
                 : "=r"(v.x), "=r"(v.y), "=r"(v.z), "=r"(v.w) : "r"(a) : "memory");
    return v;
}
__device__ __forceinline__ uint4 ldg128_nc(const void* p) {
    uint4 v;
    asm volatile("ld.global.nc.L1::no_allocate.v4.u32 {%0,%1,%2,%3}, [%4];"
                 : "=r"(v.x), "=r"(v.y), "=r"(v.z), "=r"(v.w) : "l"(p));
    return v;
}
__device__ __forceinline__ uint32_t pack_bf16(float lo, float hi) {
    uint32_t r;
    asm("cvt.rn.bf16x2.f32 %0, %1, %2;" : "=r"(r) : "f"(hi), "f"(lo));
    return r;
}
__device__ __forceinline__ float round_bf16(float v) { return __uint_as_float(pack_bf16(0.f, v) & 0xFFFF0000u); }
__device__ __forceinline__ float ex2(float x) {
    float y;
    asm("ex2.approx.ftz.f32 %0, %1;" : "=f"(y) : "f"(x));
    return y;
}
__device__ __forceinline__ uint32_t fu(float v) { return __float_as_uint(v); }

__global__ void __launch_bounds__(NTHREADS, 2)
decode_kernel(const __nv_bfloat16* __restrict__ x, const __nv_bfloat16* __restrict__ kc, const __nv_bfloat16* __restrict__ wq,
              __nv_bfloat16* __restrict__ out, const __grid_constant__ CUtensorMap wq_map,
              const __grid_constant__ CUtensorMap wo_map, const __grid_constant__ CUtensorMap v_map) {
    extern __shared__ __align__(1024) unsigned char smem[];
    const uint32_t sb = (uint32_t)__cvta_generic_to_shared(smem);
    const int warp = threadIdx.x >> 5, lane = threadIdx.x & 31;
    const int cta = blockIdx.x;
    const int gk = cta >> 4, r = cta & 15, b = r >> 2, s = r & 3;
    uint32_t spins = 0;
    const bool proj = r < 14;
    const int c = r - 7 * (r >= 7);
    const uint32_t full = sb + OFF_BAR, vfull = full + 12 * 8, empty = full + 28 * 8;
    const uint32_t qbar = empty + 14 * 8, stbar = qbar + 8, obar = qbar + 16, hbar = qbar + 24;

    if (threadIdx.x >= 32 && threadIdx.x < 32 + PFN)
        asm volatile("prefetch.global.L2 [%0];" ::"l"(kc + ((size_t)((b * 8 + gk) * SK + WIN0 + s * 256) * 256 + (threadIdx.x - 32) * 64)));
    if (warp == 0) {
        const int row0 = (b * 8 + gk) * SK + WIN0 + s * 256;
        const int worow = (2 * gk + (r >= 7)) * 256;
        const char* kp = (const char*)kc + (size_t)row0 * 512;
        const bool leader = elect_one();
        if (leader) {
            mbar_init(full + 8, 1);
            mbar_init(full + 16, 1);
            mbar_expect_tx(full + 8, 28672);
            tma2d(sb, &wq_map, (cta >> 1) * 64, (cta & 1) * 224, full + 8);
            if (proj) {
                mbar_expect_tx(full + 16, 16384);
                tma2d(sb + 2 * SLOT, &wo_map, c * 64, worow, full + 16);
            } else {
                mbar_arrive(full + 16);
            }
            fence_mbar_init();
        }
        const uint32_t c0 = (uint32_t)clock();
        __syncwarp();
        cluster_arrive();
        cluster_wait();
        if (leader) {
            const uint32_t sbp = sb;
            if (proj) mbar_expect_tx(full + 24, 16384); else mbar_arrive(full + 24);
            mbar_expect_tx(full + 32, 16384);
            while ((uint32_t)clock() - c0 < (uint32_t)PACE0) {}
            if (proj) tma2d(sbp + 3 * SLOT, &wo_map, c * 64, worow + 128, full + 24);
            while ((uint32_t)clock() - c0 < (uint32_t)(PACE0 + PACE)) {}
            bulk_g2s(sbp + 4 * SLOT, kp, 16384, full + 32);
            uint32_t bar = full + 40, dst = sbp + 5 * SLOT;
#pragma unroll 1
            for (int i = 5; i < 12; i++) {
                mbar_expect_tx(bar, 16384);
                kp += 16384;
                if (!SKEL && i >= NSLOT) mbar_wait(bar + 8 * (28 - NSLOT));
                mbar_wait(bar - 8 * 4);
                TP(i);
                bulk_g2s(dst, kp, 16384, bar);
                bar += 8;
                dst = (i == 5) ? sbp : dst + SLOT;
            }
            const int winv = (gk == 7) ? WINV7 : WINV;
            int row = row0;
            dst = sbp;
#pragma unroll 1
            for (int k = 0; k < 16; k++) {
                mbar_expect_tx(bar, 8192);
                if (!SKEL) mbar_wait(empty + 8 * (6 + (k >> 1)));
                const int d = k - winv;
                mbar_wait(vfull + 8 * (d < 0 ? (d >> 1) : d));
                TP(12 + k);
                tma3d(dst, &v_map, row, bar);
                bar += 8;
                row += 16;
                dst = (k == 11) ? sbp : dst + 8192;
            }
        }
        __syncwarp();
        if (SKEL) { for (int i = 1; i < 28; i++) mbar_wait(full + 8 * i); }
        __syncwarp();
        TS(12);
        PROF_DUMP();
        return;
    }

    const int w = warp - 1, j = threadIdx.x - 32;
    const int g = lane >> 2, t = lane & 3;
    const uint32_t sel0 = pin((g & 1) ? 0x1044u : 0x4410u);
    const uint32_t sel1 = pin((g & 1) ? 0x3244u : 0x4432u);

    const int hsel = (g >> 1) & 1;
    if (w < 7) {
        cluster_arrive();
        const uint32_t* xp = (const uint32_t*)(x + (g >> 1) * 448 + (cta & 1) * 224 + w * 32) + t;
        uint32_t xw[4];
#pragma unroll
        for (int i = 0; i < 4; i++) xw[i] = __ldg(xp + 4 * i);
        cluster_wait();
        SKEL_EXIT();
        const uint32_t qbase = sb + (w * 32 + 2 * t) * 128 + hsel * 8;
        mbar_wait(full + 8);
        float c0[4] = {0.f, 0.f, 0.f, 0.f}, c1[4] = {0.f, 0.f, 0.f, 0.f};
#pragma unroll
        for (int i = 0; i < 4; i++) {
            const uint32_t r0 = qbase + i * 1024 + ((g ^ (2 * t)) << 4), r1 = qbase + i * 1024 + 128 + ((g ^ (2 * t + 1)) << 4);
            const uint2 a0 = lds64(r0), a1 = lds64(r1), a2 = lds64(r0 ^ 8), a3 = lds64(r1 ^ 8);
            const uint32_t b0 = prmt(xw[i], sel0), b1 = prmt(xw[i], sel1);
            mma16816(c0, a0.x, a0.y, a1.x, a1.y, b0, b1);
            mma16816(c1, a2.x, a2.y, a3.x, a3.y, b0, b1);
        }
        __syncwarp();
        if (lane == 0) mbar_arrive(empty + 8 * (w >> 2));
        const uint32_t qr = sb + OFF_QRED + w * 1024 + lane * 16;
        sts128f(qr + hsel * 512, c0[0], c0[1], c0[2], c0[3]);
        sts128f(qr + (hsel ^ 1) * 512, c1[0], c1[1], c1[2], c1[3]);
    } else {
        if (lane == 0) {
#pragma unroll
            for (int i = 3; i < 28; i++) mbar_init(full + 8 * i, 1);
#pragma unroll
            for (int i = 0; i < 14; i++) mbar_init(empty + 8 * i, i == 1 ? 3 : (i < 12 ? 4 : 8));
#pragma unroll
            for (int i = 0; i < 7; i++) mbar_init(qbar + 8 * i, 1);
            mbar_expect_tx(qbar, 4096);
            mbar_expect_tx(stbar, 64);
            mbar_expect_tx(obar, 2048);
#pragma unroll
            for (int i = 0; i < 4; i++) mbar_expect_tx(hbar + 8 * i, 512);
            fence_mbar_init();
            asm volatile("prefetch.tensormap [%0];" ::"l"(&v_map) : "memory");
        }
        __syncwarp();
        cluster_arrive();
        cluster_wait();
        SKEL_EXIT();
    }
    TS(0);
    bar_sync(1, 256);
    uint2 wa[16];
    {
        const int pk = j >> 2, lp = pk & 31, hf = pk >> 5;
        const uint32_t qa = sb + OFF_QRED + pk * 16;
        float4 a = lds128f(qa);
#pragma unroll
        for (int ww = 1; ww < 7; ww++) {
            const float4 v = lds128f(qa + ww * 1024);
            a.x += v.x; a.y += v.y; a.z += v.z; a.w += v.w;
        }
        const uint32_t dst = (lp & 3) * 4 + (j & 3);
        st_async128(mapa(sb + OFF_QBUF + ((r & 1) * 512 + (r >> 1) * 64 + (lp >> 2) * 8 + hf * 4) * 4, dst),
                    fu(a.x), fu(a.y), fu(a.z), fu(a.w), mapa(qbar, dst));
        {
            const int sw = 2 + (w >> 2);
            mbar_wait(full + 8 * sw);
            if (proj) {
                const uint32_t wbase = sb + sw * SLOT + (((w >> 1) & 1) * 64 + 2 * t) * 128 + (g & 1) * 8;
                const uint32_t ck = (w & 1) * 4 + (g >> 1);
#pragma unroll
                for (int m = 0; m < 16; m++)
                    wa[m] = lds64(wbase + ((m >> 3) * 32 + ((m >> 2) & 1) + 8 * (m & 3)) * 128 + ((ck ^ (2 * t + ((m >> 2) & 1))) << 4));
                uint32_t dep = 0;
#pragma unroll
                for (int m = 0; m < 16; m++) dep ^= wa[m].x;
                pin(dep);
            }
            __syncwarp();
            if (lane == 0) mbar_arrive(empty + 8 * sw);
            TS(4);
        }
        mbar_wait(qbar);
        const float2 u = lds64f(sb + OFF_QBUF + j * 8), v = lds64f(sb + OFF_QBUF + 2048 + j * 8);
        sts32(sb + OFF_QS + ((j >> 5) & 3) * 256 + (j & 1) * 128 + (j >> 7) * 64 + ((j >> 2) & 3) * 16 + ((j >> 4) & 1) * 8 + ((j >> 1) & 1) * 4,
              pack_bf16(u.x + v.x, u.y + v.y));
    }
    bar_sync(1, 256);
    TS(1);

    float s0 = 0.f, s1 = 0.f;
    {
        uint2 qf[8];
        const uint32_t qa = sb + OFF_QS + (g >> 2) * 128 + (g & 1) * 64 + t * 16;
        const uint32_t qx = ((g >> 1) & 1) * 8;
#pragma unroll
        for (int i = 0; i < 8; i++) qf[i] = lds64(qa + (i >> 1) * 256 + (((i & 1) * 8) ^ qx));
        const uint32_t kx = (g & 1) * 64;
        const uint32_t krow = sb + ((w & 3) * 8 + g) * 512 + t * 16;
        const int src = (lane & 28) + (g & 1);
#pragma unroll 1
        for (int k = 0; k < 4; k++) {
            const int st = 4 + 2 * k + (w >> 2);
            const uint32_t ka = krow + (st >= NSLOT ? st - NSLOT : st) * SLOT;
            mbar_wait(full + 8 * st);
            float a0[4] = {0.f, 0.f, 0.f, 0.f}, a1[4] = {0.f, 0.f, 0.f, 0.f};
#pragma unroll
            for (int i = 0; i < 8; i += 2) {
                const uint4 r0 = lds128(ka + ((i * 64) ^ kx)), r1 = lds128(ka + (((i + 1) * 64) ^ kx));
                mma16816(a0, r0.x, r0.y, r0.z, r0.w, qf[i].x, qf[i].y);
                mma16816(a1, r1.x, r1.y, r1.z, r1.w, qf[i + 1].x, qf[i + 1].y);
            }
            const float e0 = __shfl_sync(0xffffffffu, a0[0] + a1[0], src) + __shfl_sync(0xffffffffu, a0[2] + a1[2], src + 2);
            const float e1 = __shfl_sync(0xffffffffu, a0[1] + a1[1], src) + __shfl_sync(0xffffffffu, a0[3] + a1[3], src + 2);
            if (lane == 0) mbar_arrive(empty + 8 * st);
            if (t == k) { s0 = e0; s1 = e1; }
            if (k == 0) TS(2);
        }
    }
    float Mown;
    {
        const float kscale = 0.0625f * 1.4426950408889634f;
        s0 = round_bf16(s0) * kscale;
        s1 = round_bf16(s1) * kscale;
        float m0 = s0, m1 = s1;
#pragma unroll
        for (int o = 16; o > 0; o >>= 1) {
            m0 = fmaxf(m0, __shfl_xor_sync(0xffffffffu, m0, o));
            m1 = fmaxf(m1, __shfl_xor_sync(0xffffffffu, m1, o));
        }
        if (lane < 2) sts32(sb + OFF_WST + (w * 2 + lane) * 4, fu(lane ? m1 : m0));
        bar_sync(1, 256);
        const float4 u0 = lds128f(sb + OFF_WST), u1 = lds128f(sb + OFF_WST + 16), u2 = lds128f(sb + OFF_WST + 32), u3 = lds128f(sb + OFF_WST + 48);
        const float M0 = fmaxf(fmaxf(fmaxf(u0.x, u0.z), fmaxf(u1.x, u1.z)), fmaxf(fmaxf(u2.x, u2.z), fmaxf(u3.x, u3.z)));
        const float M1 = fmaxf(fmaxf(fmaxf(u0.y, u0.w), fmaxf(u1.y, u1.w)), fmaxf(fmaxf(u2.y, u2.w), fmaxf(u3.y, u3.w)));
        Mown = (t & 1) ? M1 : M0;
        const uint32_t p = pack_bf16(ex2(s0 - M0), ex2(s1 - M1));
        const uint32_t pa = sb + OFF_PS + (4 * t + (w >> 1)) * 64 + (g >> 1) * 8 + (w & 1) * 4 + (g & 1) * 2;
        sts16(pa, (unsigned short)(p & 0xFFFFu));
        sts16(pa + 32, (unsigned short)(p >> 16));
        float l0 = __uint_as_float(p << 16), l1 = __uint_as_float(p & 0xFFFF0000u);
#pragma unroll
        for (int o = 16; o > 0; o >>= 1) {
            l0 += __shfl_xor_sync(0xffffffffu, l0, o);
            l1 += __shfl_xor_sync(0xffffffffu, l1, o);
        }
        if (lane < 2) sts32(sb + OFF_WST + 64 + (w * 2 + lane) * 4, fu(lane ? l1 : l0));
        bar_sync(1, 256);
        if (j < 4) {
            const float4 v0 = lds128f(sb + OFF_WST + 64), v1 = lds128f(sb + OFF_WST + 80), v2 = lds128f(sb + OFF_WST + 96), v3 = lds128f(sb + OFF_WST + 112);
            const float L0 = ((v0.x + v0.z) + (v1.x + v1.z)) + ((v2.x + v2.z) + (v3.x + v3.z));
            const float L1 = ((v0.y + v0.w) + (v1.y + v1.w)) + ((v2.y + v2.w) + (v3.y + v3.w));
            st_async128(mapa(sb + OFF_WST + 128 + s * 16, b * 4 + j), fu(M0), fu(L0), fu(M1), fu(L1), mapa(stbar, b * 4 + j));
        }
    }
    TS(3);

    const uint32_t h1_dst = pin(mapa(sb + OFF_HOP + r * 128 + g * 16 + (t >> 1) * 8, (t & 1) * 8 + w));
    const uint32_t h1_bar = pin(mapa(hbar + 8 * b, (t & 1) * 8 + w));
    const uint32_t h2_grp = (w >> 2) * 4 + (lane >> 3);
    const uint32_t h2_rank = h2_grp < 7 ? (r >> 3) * 7 + h2_grp : 14 + (r >> 3);
    const uint32_t h2_dst = pin(mapa(sb + OFF_OB + (w & 3) * 512 + (r & 7) * 64 + (lane & 7) * 8, h2_rank));
    const uint32_t h2_bar = pin(mapa(obar, h2_rank));
    const uint32_t h2_src = pin(sb + OFF_HOP + (w & 3) * 512 + (lane & 7) * 16);
    const uint32_t h2_wait = pin(hbar + 8 * (w & 3));
    const uint32_t bars = pin(obar);
    const uint32_t ob_src = pin(sb + OFF_OB + (g >> 1) * 512 + (w >> 1) * 128 + t * 16);
    const uint32_t red_st = pin(sb + w * 512 + t * 128 + ((g ^ (2 * t)) * 16));
    const uint32_t red_ld = pin(sb + (w >> 2) * 512 + (w & 3) * 128 + ((g ^ (2 * (w & 3))) * 16) + t * 4);
    unsigned long long* acc_p = pin_ptr(&g_acc[ACC_IDX(c, j)]);
    __nv_bfloat16* out_p = pin_ptr(out + (w & 3) * 448 + c * 64 + (w >> 2) * 32 + lane);
    const bool h1_hi = pin(t >> 1) != 0, proj_on = pin(proj ? 1u : 0u) != 0;

    float acc0[4] = {0.f, 0.f, 0.f, 0.f}, acc1[4] = {0.f, 0.f, 0.f, 0.f};
    float wgt = 0.f;
    {
        const uint32_t voff = sb + (w >> 1) * 2048 + ((lane >> 4) * 8 + (lane & 7)) * 128;
        const uint32_t va0 = pin(voff + ((((w & 1) * 4 + ((lane >> 3) & 1)) ^ (lane & 7)) << 4));
        const uint32_t va1 = pin(va0 ^ 32);
        const uint32_t pa = pin(sb + OFF_PS + ((g >> 1) & 1) * 32 + t * 8);
        const uint32_t vb = bars - (obar - vfull);
        bool ok = mbar_try(vb);
        uint2 pw = lds64(pa);
#pragma unroll
        for (int k = 0; k < 16; k++) {
            const uint32_t so = (k < 12 ? k : k - 12) * 8192;
            if (!ok) mbar_wait_t(vb + 8 * k);
            if (k == 15) TC(16);
            const uint4 f0 = ldsm4t(va0 + so), f1 = ldsm4t(va1 + so);
            const uint2 pc = pw;
            if (k < 15) {
                if (k != 1 && k != 3 && k != 7) ok = mbar_try(vb + 8 * k + 8);
                pw = lds64(pa + k * 64 + 64);
            }
            mma16816(acc0, f0.x, f0.y, f0.z, f0.w, pc.x, pc.y);
            mma16816(acc1, f1.x, f1.y, f1.z, f1.w, pc.x, pc.y);
            if (k == 1 || k == 3) {
                __syncwarp();
                if (lane == 0) mbar_arrive(empty + 8 * (12 + (k >> 1)));
                ok = mbar_try(vb + 8 * k + 8);
            }
            if (k == 7) {
                mbar_wait(stbar);
                const uint32_t sa = sb + OFF_WST + 128 + (t & 1) * 8;
                const float2 z0 = lds64f(sa), z1 = lds64f(sa + 16), z2 = lds64f(sa + 32), z3 = lds64f(sa + 48);
                ok = mbar_try(vb + 8 * k + 8);
                const float mx = fmaxf(fmaxf(z0.x, z1.x), fmaxf(z2.x, z3.x));
                const float W = (ex2(z0.x - mx) * z0.y + ex2(z1.x - mx) * z1.y) + (ex2(z2.x - mx) * z2.y + ex2(z3.x - mx) * z3.y);
                wgt = __uint_as_float(pin(fu(__fdividef(ex2(Mown - mx), W))));
            }
        }
    }
    st_async64(h1_dst, fu((h1_hi ? acc1[0] : acc0[0]) * wgt), fu((h1_hi ? acc1[2] : acc0[2]) * wgt), h1_bar);
    TC(17);
    {
        mbar_wait_t(h2_wait);
        TC(18);
        const float4 v0 = lds128f(h2_src), v1 = lds128f(h2_src + 128), v2 = lds128f(h2_src + 256), v3 = lds128f(h2_src + 384);
        st_async64(h2_dst, pack_bf16((v0.x + v1.x) + (v2.x + v3.x), (v0.y + v1.y) + (v2.y + v3.y)),
                      pack_bf16((v0.z + v1.z) + (v2.z + v3.z), (v0.w + v1.w) + (v2.w + v3.w)), h2_bar);
    }
    TC(19);
    mbar_wait_t(bars);
    if (proj_on) {
        TC(20);
        const uint4 oa = lds128(ob_src), ob = lds128(ob_src + 64);
        const uint32_t ow[8] = {oa.x, oa.y, oa.z, oa.w, ob.x, ob.y, ob.z, ob.w};
        float d[4][4];
#pragma unroll
        for (int i = 0; i < 4; i++) d[i][0] = d[i][1] = d[i][2] = d[i][3] = 0.f;
#pragma unroll
        for (int i = 0; i < 8; i++)
            mma16816(d[i & 3], wa[2 * i].x, wa[2 * i].y, wa[2 * i + 1].x, wa[2 * i + 1].y,
                     prmt(ow[i], sel0), prmt(ow[i], sel1));
        sts128f(red_st, (d[0][0] + d[1][0]) + (d[2][0] + d[3][0]), (d[0][1] + d[1][1]) + (d[2][1] + d[3][1]),
                (d[0][2] + d[1][2]) + (d[2][2] + d[3][2]), (d[0][3] + d[1][3]) + (d[2][3] + d[3][3]));
        TC(21);
        bar_sync(1, 256);
        const float sum = (lds32f(red_ld) + lds32f(red_ld + 1024)) + (lds32f(red_ld + 2048) + lds32f(red_ld + 3072));
        const uint32_t bits = fu(sum);
        const uint32_t sh = ((bits >> 23) & 0xFFu) - 94u;
        if (sh > 35u) { accumulate_slow(sum, acc_p, out_p); return; }
        const int mant = (int)((bits & 0x7FFFFFu) | 0x800000u);
        const int smant = ((int)bits < 0) ? -mant : mant;
        const unsigned long long inc = (((unsigned long long)(long long)smant << sh) & ~0x3FFull) | 1ull;
        TC(22);
        unsigned long long tot;
        asm volatile("atom.relaxed.gpu.global.add.u64 %0, [%1], %2;" : "=l"(tot) : "l"(acc_p), "l"(inc) : "memory");
        tot += inc;
        const uint32_t cnt = (uint32_t)tot & 0x3FFu;
        asm volatile("{\n.reg .pred p;\nsetp.eq.u32 p, %3, 16;\n@p st.global.u16 [%0], %1;\n@p st.global.u64 [%2], 0;\n}"
                     ::"l"(out_p), "h"(__bfloat16_as_ushort(__float2bfloat16(acc_value(tot)))), "l"(acc_p), "r"(cnt) : "memory");
        if (cnt > 16u) finish_with_side(tot, acc_p, out_p);
        TC(23);
        TS(9);
    }
    TC_DUMP();
    PROF_DUMP();
}

typedef CUresult (*EncodeFn)(CUtensorMap*, CUtensorMapDataType, cuuint32_t, void*, const cuuint64_t*, const cuuint64_t*,
                             const cuuint32_t*, const cuuint32_t*, CUtensorMapInterleave, CUtensorMapSwizzle,
                             CUtensorMapL2promotion, CUtensorMapFloatOOBfill);

}

extern "C" void kernel_launch(void* const* d_in, const int* in_sizes, int n_in, void* d_out, int out_size) {
    (void)in_sizes; (void)n_in; (void)out_size;
    static EncodeFn encode = nullptr;
    if (!encode) {
        cudaDriverEntryPointQueryResult qr;
        cudaGetDriverEntryPoint("cuTensorMapEncodeTiled", (void**)&encode, cudaEnableDefault, &qr);
        cudaFuncSetAttribute(decode_kernel, cudaFuncAttributeMaxDynamicSharedMemorySize, SMEM_BYTES);
        cudaFuncSetAttribute(decode_kernel, cudaFuncAttributeNonPortableClusterSizeAllowed, 1);
    }
    CUtensorMap wo_map;
    const cuuint64_t gdim[2] = {448, 4096};
    const cuuint64_t gstr[1] = {896};
    const cuuint32_t box[2] = {64, 128};
    const cuuint32_t estr[2] = {1, 1};
    encode(&wo_map, CU_TENSOR_MAP_DATA_TYPE_BFLOAT16, 2, d_in[4], gdim, gstr, box, estr, CU_TENSOR_MAP_INTERLEAVE_NONE,
           CU_TENSOR_MAP_SWIZZLE_128B, CU_TENSOR_MAP_L2_PROMOTION_NONE, CU_TENSOR_MAP_FLOAT_OOB_FILL_NONE);

    CUtensorMap wq_map;
    const cuuint64_t qdim[2] = {4096, 448};
    const cuuint64_t qstr[1] = {8192};
    const cuuint32_t qbox[2] = {64, 224};
    encode(&wq_map, CU_TENSOR_MAP_DATA_TYPE_BFLOAT16, 2, d_in[3], qdim, qstr, qbox, estr, CU_TENSOR_MAP_INTERLEAVE_NONE,
           CU_TENSOR_MAP_SWIZZLE_128B, CU_TENSOR_MAP_L2_PROMOTION_NONE, CU_TENSOR_MAP_FLOAT_OOB_FILL_NONE);
    CUtensorMap v_map;
    const cuuint64_t vdim[3] = {64, 4ull * 8 * SK, 4};
    const cuuint64_t vstr[2] = {512, 128};
    const cuuint32_t vbox[3] = {64, 16, 4};
    const cuuint32_t vestr[3] = {1, 1, 1};
    encode(&v_map, CU_TENSOR_MAP_DATA_TYPE_BFLOAT16, 3, d_in[2], vdim, vstr, vbox, vestr, CU_TENSOR_MAP_INTERLEAVE_NONE,
           CU_TENSOR_MAP_SWIZZLE_128B, (CUtensorMapL2promotion)VPROMO, CU_TENSOR_MAP_FLOAT_OOB_FILL_NONE);

    cudaLaunchConfig_t cfg = {};
    cfg.gridDim = dim3(128);
    cfg.blockDim = dim3(NTHREADS);
    cfg.dynamicSmemBytes = SMEM_BYTES;
    cfg.stream = cudaStreamPerThread;
    cudaLaunchAttribute attr[2];
    attr[0].id = cudaLaunchAttributeClusterDimension;
    attr[0].val.clusterDim.x = CLDIM; attr[0].val.clusterDim.y = 1; attr[0].val.clusterDim.z = 1;
    attr[1].id = cudaLaunchAttributeClusterSchedulingPolicyPreference;
    attr[1].val.clusterSchedulingPolicyPreference = cudaClusterSchedulingPolicyLoadBalancing;
    cfg.attrs = attr;
    cfg.numAttrs = 2;
    cudaLaunchKernelEx(&cfg, decode_kernel, (const __nv_bfloat16*)d_in[0], (const __nv_bfloat16*)d_in[1], (const __nv_bfloat16*)d_in[3],
                       (__nv_bfloat16*)d_out, wq_map, wo_map, v_map);
}
```

```cpp
#include <cuda_runtime.h>
#include <cuda_bf16.h>
#include <cuda.h>
#include <stdint.h>

namespace {

constexpr int SK = 4096, WIN0 = 3072;
constexpr int SLOT = 16384;
constexpr int NSLOT = 6;
constexpr int OFF_BAR  = NSLOT * SLOT;
constexpr int OFF_QBUF = OFF_BAR + 416;
constexpr int OFF_QS   = OFF_QBUF + 4096;
constexpr int OFF_WST  = OFF_QS + 1024;
constexpr int OFF_OB   = OFF_WST + 192;
constexpr int OB_STRIDE = 576;
constexpr int OFF_HOP  = OFF_OB + 4 * OB_STRIDE;
constexpr int OFF_QRED = OFF_HOP + 2048;
constexpr int OFF_PS   = OFF_QRED;
constexpr int OFF_PROF = OFF_QRED + 7 * 1024;
constexpr int SMEM_BYTES = OFF_PROF;
static_assert(SMEM_BYTES <= 115712, "two CTAs must fit on one SM");
constexpr int NTHREADS = 288;
constexpr int SPIN_LIMIT = 1 << 20;

#define WINK 8
#define WINV 7
#define COUNTWIN 0
#define PSLEEP 50
#define CSLEEP 50
#define K0FIRST 0
#define WARM 0
#define SKEL 0
#define CLDIM 16
#define WINV7 12
#define NOST 0
#define OMAP 1
#define PF 7
#define PFN 64
#define UNB 1
#define ACCPARAM 1
#define XM 4
#define VPF 1
#define XPF 0
#define ZWAIT 7
#define WK 4
#define WK7 6
#define PACE07 0
#define PACE7 0
#define ZDELAY 0
#define ZCTA 0
#define VORD 0
#define TV0 6700
#define TDV 332
#define T7 1600
#define WLK 2
#define WLV 4
#define PSL 0
#define TSTAG 0
#define NPACED 4
#define NORD 16
#define PACE0 700
#define PACE 1300
#define VPROMO 0
#define ST_TRIG 8

#define AG 16
#define AS 32
#define ACC_IDX(c, j) ((((c) * 256 + (j)) / AG) * AS + (j) % AG)
constexpr int ACC_WORDS = 1792 / AG * AS;
__device__ __align__(1024) unsigned long long g_acc[ACC_WORDS];
__device__ float g_side[ACC_WORDS];

#define GT_AT(n)
#define GT_END()
#define SKEL_EXIT() do { if (SKEL) return; } while (0)
#define TS(i)
#define TC(i)
#define TC_DUMP()
#define TP(i)
#define PROF_DUMP()

__device__ __forceinline__ void mbar_init(uint32_t bar, uint32_t cnt) {
    asm volatile("mbarrier.init.shared::cta.b64 [%0], %1;" ::"r"(bar), "r"(cnt) : "memory");
}
__device__ __forceinline__ void mbar_expect_tx(uint32_t bar, uint32_t bytes) {
    asm volatile("mbarrier.arrive.expect_tx.shared::cta.b64 _, [%0], %1;" ::"r"(bar), "r"(bytes) : "memory");
}
__device__ __forceinline__ void mbar_arrive(uint32_t bar) {
    asm volatile("mbarrier.arrive.shared::cta.b64 _, [%0];" ::"r"(bar) : "memory");
}
__device__ __forceinline__ void slot_release(uint32_t bar, uint32_t dep, uint32_t zero, int lane) {
    if (lane == 0) mbar_arrive(bar + (dep & zero));
}
__device__ __forceinline__ void mbar_wait_n(uint32_t bar, uint32_t& n) {
    asm volatile("{\n.reg .pred p, q;\n"
                 "WAIT_LOOP:\n"
                 "mbarrier.try_wait.parity.shared::cta.b64 p, [%1], 0;\n"
                 "add.u32 %0, %0, 1;\n"
                 "setp.lt.and.u32 q, %0, %2, !p;\n"
                 "@q bra.uni WAIT_LOOP;\n}"
                 : "+r"(n) : "r"(bar), "n"(SPIN_LIMIT) : "memory");
}
__device__ __forceinline__ void mbar_wait_u(uint32_t bar) {
    asm volatile("{\n.reg .pred p;\nWAIT_LOOP:\nmbarrier.try_wait.parity.shared::cta.b64 p, [%0], 0;\n@!p bra.uni WAIT_LOOP;\n}" ::"r"(bar) : "memory");
}
#define mbar_wait(bar) mbar_wait_n(bar, spins)
#define mbar_wait_t(bar) mbar_wait_u(bar)
__device__ __forceinline__ bool mbar_try(uint32_t bar) {
    uint32_t ok;
    asm volatile("{\n.reg .pred p;\nmbarrier.try_wait.parity.shared::cta.b64 p, [%1], 0;\nselp.u32 %0, 1, 0, p;\n}"
                 : "=r"(ok) : "r"(bar) : "memory");
    return ok != 0;
}
__device__ __forceinline__ uint32_t now_ns() {
    uint32_t t;
    asm volatile("mov.u32 %0, %%globaltimer_lo;" : "=r"(t));
    return t;
}
__device__ __forceinline__ void pace(uint32_t due, uint32_t bar) {
    while ((int)(now_ns() - due) < 0) {
        uint32_t ok;
        asm volatile("{\n.reg .pred p;\nmbarrier.test_wait.parity.shared::cta.b64 p, [%1], 0;\nselp.u32 %0, 1, 0, p;\n}"
                     : "=r"(ok) : "r"(bar) : "memory");
        if (ok) break;
    }
}
__device__ __forceinline__ void bulk_g2s(uint32_t dst, const void* src, uint32_t bytes, uint32_t bar) {
    asm volatile("cp.async.bulk.shared::cluster.global.mbarrier::complete_tx::bytes [%0], [%1], %2, [%3];"
                 ::"r"(dst), "l"(src), "r"(bytes), "r"(bar) : "memory");
}
__device__ __forceinline__ void bulk_g2s_mc(uint32_t dst, const void* src, uint32_t bytes, uint32_t bar, uint16_t mask) {
    asm volatile("cp.async.bulk.shared::cluster.global.mbarrier::complete_tx::bytes.multicast::cluster [%0], [%1], %2, [%3], %4;"
                 ::"r"(dst), "l"(src), "r"(bytes), "r"(bar), "h"(mask) : "memory");
}
__device__ __forceinline__ void tma2d(uint32_t dst, const CUtensorMap* tm, int c0, int c1, uint32_t bar) {
    asm volatile("cp.async.bulk.tensor.2d.shared::cluster.global.mbarrier::complete_tx::bytes [%0], [%1, {%3, %4}], [%2];"
                 ::"r"(dst), "l"(tm), "r"(bar), "r"(c0), "r"(c1) : "memory");
}
__device__ __forceinline__ void tma3d(uint32_t dst, const CUtensorMap* tm, int c1, uint32_t bar) {
    asm volatile("cp.async.bulk.tensor.3d.shared::cluster.global.mbarrier::complete_tx::bytes [%0], [%1, {%3, %4, %3}], [%2];"
                 ::"r"(dst), "l"(tm), "r"(bar), "r"(0), "r"(c1) : "memory");
}
__device__ __forceinline__ uint32_t pin(uint32_t v) {
    uint32_t o;
    asm volatile("shfl.sync.bfly.b32 %0, %1, 0, 0x1f, 0xffffffff;" : "=r"(o) : "r"(v));
    return o;
}
template <typename T> __device__ __forceinline__ T* pin_ptr(T* p) {
    const unsigned long long a = (unsigned long long)p;
    return (T*)(((unsigned long long)pin((uint32_t)(a >> 32)) << 32) | pin((uint32_t)a));
}
__device__ __forceinline__ bool elect_one() {
    uint32_t p;
    asm volatile("{\n.reg .pred P;\nelect.sync _|P, 0xffffffff;\nselp.u32 %0, 1, 0, P;\n}" : "=r"(p));
    return p != 0;
}
__device__ __forceinline__ void bar_sync(int id, int n) { asm volatile("bar.sync %0, %1;" ::"r"(id), "r"(n) : "memory"); }
__device__ __forceinline__ void cluster_arrive() { asm volatile("barrier.cluster.arrive.relaxed.aligned;" ::: "memory"); }
__device__ __forceinline__ void cluster_wait() { asm volatile("barrier.cluster.wait.aligned;" ::: "memory"); }
__device__ __forceinline__ void fence_mbar_init() { asm volatile("fence.mbarrier_init.release.cluster;" ::: "memory"); }
__device__ __forceinline__ uint32_t mapa(uint32_t a, uint32_t rank) {
    uint32_t o;
    asm("mapa.shared::cluster.u32 %0, %1, %2;" : "=r"(o) : "r"(a), "r"(rank));
    return o;
}
__device__ __forceinline__ void st_async128(uint32_t a, uint32_t x, uint32_t y, uint32_t z, uint32_t w, uint32_t bar) {
    asm volatile("st.async.shared::cluster.mbarrier::complete_tx::bytes.v4.b32 [%0], {%1,%2,%3,%4}, [%5];"
                 ::"r"(a), "r"(x), "r"(y), "r"(z), "r"(w), "r"(bar) : "memory");
}
__device__ __forceinline__ void st_async64(uint32_t a, uint32_t x, uint32_t y, uint32_t bar) {
    asm volatile("st.async.shared::cluster.mbarrier::complete_tx::bytes.v2.b32 [%0], {%1,%2}, [%3];"
                 ::"r"(a), "r"(x), "r"(y), "r"(bar) : "memory");
}

__device__ __forceinline__ uint32_t prmt(uint32_t a, uint32_t sel) {
    uint32_t o;
    asm("prmt.b32 %0, %1, 0, %2;" : "=r"(o) : "r"(a), "r"(sel));
    return o;
}
__device__ __forceinline__ float acc_value(unsigned long long tot) {
    return fmaf((float)(int)(uint32_t)(tot >> 32), 0x1p-24f, (float)((uint32_t)tot >> 10) * 0x1p-46f);
}
__device__ __noinline__ void finish_with_side(unsigned long long tot, unsigned long long* acc_p, __nv_bfloat16* out_p) {
    if ((tot & 31ull) != 16ull) return;
    __threadfence();
    const float side = atomicExch(&g_side[acc_p - g_acc], 0.0f);
    *out_p = __float2bfloat16(acc_value(tot) + side);
    *acc_p = 0ull;
}
__device__ __noinline__ void accumulate_slow(float sum, unsigned long long* acc_p, __nv_bfloat16* out_p) {
    atomicAdd(&g_side[acc_p - g_acc], sum);
    __threadfence();
    finish_with_side(atomicAdd(acc_p, 33ull) + 33ull, acc_p, out_p);
}

__device__ __forceinline__ void mma16816(float (&c)[4], uint32_t a0, uint32_t a1, uint32_t a2, uint32_t a3,
                                         uint32_t b0, uint32_t b1) {
    asm volatile("mma.sync.aligned.m16n8k16.row.col.f32.bf16.bf16.f32 {%0,%1,%2,%3}, {%4,%5,%6,%7}, {%8,%9}, {%0,%1,%2,%3};"
                 : "+f"(c[0]), "+f"(c[1]), "+f"(c[2]), "+f"(c[3])
                 : "r"(a0), "r"(a1), "r"(a2), "r"(a3), "r"(b0), "r"(b1));
}
__device__ __forceinline__ uint4 lds128(uint32_t a) {
    uint4 v;
    asm volatile("ld.shared.v4.u32 {%0,%1,%2,%3}, [%4];" : "=r"(v.x), "=r"(v.y), "=r"(v.z), "=r"(v.w) : "r"(a) : "memory");
    return v;
}
__device__ __forceinline__ float4 lds128f(uint32_t a) {
    float4 v;
    asm volatile("ld.shared.v4.f32 {%0,%1,%2,%3}, [%4];" : "=f"(v.x), "=f"(v.y), "=f"(v.z), "=f"(v.w) : "r"(a) : "memory");
    return v;
}
__device__ __forceinline__ float2 lds64f(uint32_t a) {
    float2 v;
    asm volatile("ld.shared.v2.f32 {%0,%1}, [%2];" : "=f"(v.x), "=f"(v.y) : "r"(a) : "memory");
    return v;
}
__device__ __forceinline__ uint2 lds64(uint32_t a) {
    uint2 v;
    asm volatile("ld.shared.v2.u32 {%0,%1}, [%2];" : "=r"(v.x), "=r"(v.y) : "r"(a) : "memory");
    return v;
}
__device__ __forceinline__ float lds32f(uint32_t a) {
    float v;
    asm volatile("ld.shared.f32 %0, [%1];" : "=f"(v) : "r"(a) : "memory");
    return v;
}
__device__ __forceinline__ void sts128f(uint32_t a, float x, float y, float z, float w) {
    asm volatile("st.shared.v4.f32 [%0], {%1,%2,%3,%4};" ::"r"(a), "f"(x), "f"(y), "f"(z), "f"(w) : "memory");
}
__device__ __forceinline__ void sts32(uint32_t a, uint32_t v) {
    asm volatile("st.shared.u32 [%0], %1;" ::"r"(a), "r"(v) : "memory");
}
__device__ __forceinline__ void sts16(uint32_t a, unsigned short v) {
    asm volatile("st.shared.u16 [%0], %1;" ::"r"(a), "h"(v) : "memory");
}
__device__ __forceinline__ uint4 ldsm4t(uint32_t a) {
    uint4 v;
    asm volatile("ldmatrix.sync.aligned.m8n8.x4.trans.shared.b16 {%0,%1,%2,%3}, [%4];"
                 : "=r"(v.x), "=r"(v.y), "=r"(v.z), "=r"(v.w) : "r"(a) : "memory");
    return v;
}
__device__ __forceinline__ uint4 ldg128_nc(const void* p) {
    uint4 v;
    asm volatile("ld.global.nc.L1::no_allocate.v4.u32 {%0,%1,%2,%3}, [%4];"
                 : "=r"(v.x), "=r"(v.y), "=r"(v.z), "=r"(v.w) : "l"(p));
    return v;
}
__device__ __forceinline__ uint32_t pack_bf16(float lo, float hi) {
    uint32_t r;
    asm("cvt.rn.bf16x2.f32 %0, %1, %2;" : "=r"(r) : "f"(hi), "f"(lo));
    return r;
}
__device__ __forceinline__ float round_bf16(float v) { return __uint_as_float(pack_bf16(0.f, v) & 0xFFFF0000u); }
__device__ __forceinline__ float ex2(float x) {
    float y;
    asm("ex2.approx.ftz.f32 %0, %1;" : "=f"(y) : "f"(x));
    return y;
}
__device__ __forceinline__ uint32_t fu(float v) { return __float_as_uint(v); }

__global__ void __launch_bounds__(NTHREADS, 2)
decode_kernel(const __nv_bfloat16* __restrict__ x, const __nv_bfloat16* __restrict__ kc, const __nv_bfloat16* __restrict__ wq,
              __nv_bfloat16* __restrict__ out, unsigned long long* __restrict__ acc, const uint32_t zero, const __grid_constant__ CUtensorMap wq_map,
              const __grid_constant__ CUtensorMap wo_map, const __grid_constant__ CUtensorMap v_map) {
    {
        const uint32_t off = (blockIdx.x * 224 + min(threadIdx.x, 223u)) * 128;
        asm volatile("prefetch.global.L2 [%0];" ::"l"((const char*)wq + off));
    }
    extern __shared__ __align__(1024) unsigned char smem[];
    const uint32_t sb = (uint32_t)__cvta_generic_to_shared(smem);
    const int warp = threadIdx.x >> 5, lane = threadIdx.x & 31;
    const int cta = blockIdx.x;
    const int gk = cta >> 4, r = cta & 15, b = r >> 2, s = r & 3;
    uint32_t spins = 0;
    const bool proj = r < 14;
    const int c = r - 7 * (r >= 7);
    const uint32_t full = sb + OFF_BAR, vfull = full + 12 * 8, empty = full + 28 * 8;
    const uint32_t qbar = empty + 14 * 8, stbar = qbar + 8, obar = qbar + 16, hbar = qbar + 24;

    if (warp == 0) {
        const int row0 = (b * 8 + gk) * SK + WIN0 + s * 256;
        const int worow = (2 * gk + (r >= 7)) * 256;
        const char* kp = (const char*)kc + (size_t)row0 * 512;
        const bool leader = elect_one();
        if (leader) {
            mbar_init(full + 8, 1);
            mbar_init(full + 16, 1);
            mbar_expect_tx(full + 8, XM >= 3 ? 28672 + 3584 : 28672);
            tma2d(sb, &wq_map, (cta >> 1) * 64, (cta & 1) * 224, full + 8);
            if (proj) {
                mbar_expect_tx(full + 16, 16384);
                tma2d(sb + 2 * SLOT, &wo_map, c * 64, worow, full + 16);
            } else {
                mbar_arrive(full + 16);
            }
            fence_mbar_init();
        }
        const uint32_t t0 = now_ns();
        __syncwarp();
        cluster_arrive();
        cluster_wait();
        if (leader) {
            const uint32_t sbp = sb;
            if (XM == 3 && r == 0) bulk_g2s_mc(sbp + OFF_OB, x, 3584, full + 8, (uint16_t)0xFFFF);
            if (XM == 4 && r < 14) bulk_g2s_mc(sbp + OFF_OB + r * 256, (const char*)x + r * 256, 256, full + 8, (uint16_t)0xFFFF);
            asm volatile("prefetch.tensormap [%0];" ::"l"(&v_map) : "memory");
            uint32_t due = t0 + (TV0 - 9 * 2 * TDV) - (gk == 7 ? T7 : gk * TSTAG);
            if (proj) mbar_expect_tx(full + 24, 16384); else mbar_arrive(full + 24);
            pace(due, full + 8);
            if (proj) tma2d(sbp + 3 * SLOT, &wo_map, c * 64, worow + 128, full + 24);
            uint32_t bar = full + 32, dst = sbp + 4 * SLOT;
#pragma unroll 1
            for (int i = 4; i < 12; i++) {
                mbar_expect_tx(bar, 16384);
                due += 2 * TDV;
                if (!SKEL && i >= NSLOT) mbar_wait(bar + 8 * (28 - NSLOT));
                pace(due, bar - 8 * WLK);
                TP(i);
                bulk_g2s(dst, kp, 16384, bar);
                kp += 16384;
                bar += 8;
                dst = (i == 5) ? sbp : dst + SLOT;
            }
            int row = row0;
            dst = sbp;
            due += TDV;
#pragma unroll 1
            for (int k = 0; k < 16; k++) {
                mbar_expect_tx(bar, 8192);
                due += TDV;
                if (!SKEL) mbar_wait(empty + 8 * (6 + (k >> 1)));
                const int d = k - WLV;
                pace(due, vfull + 8 * (d < 0 ? (d >> 1) : d));
                TP(12 + k);
                tma3d(dst, &v_map, row, bar);
                bar += 8;
                row += 16;
                dst = (k == 11) ? sbp : dst + 8192;
            }
        }
        __syncwarp();
        if (SKEL) { for (int i = 1; i < 28; i++) mbar_wait(full + 8 * i); }
        __syncwarp();
        TS(12);
        PROF_DUMP();
        return;
    }

    const int w = warp - 1, j = threadIdx.x - 32;
    const int g = lane >> 2, t = lane & 3;
    const uint32_t sel0 = pin((g & 1) ? 0x1044u : 0x4410u);
    const uint32_t sel1 = pin((g & 1) ? 0x3244u : 0x4432u);

    const int hsel = (g >> 1) & 1;
    if (w < 7) {
        cluster_arrive();
        const uint32_t* xp = (const uint32_t*)(x + (g >> 1) * 448 + (cta & 1) * 224 + w * 32) + t;
        uint32_t xw[4];
#pragma unroll
        for (int i = 0; i < 4; i++) xw[i] = (XM == 0) ? __ldg(xp + 4 * i) : 0x3c003c00u + lane;
        cluster_wait();
        SKEL_EXIT();
        const uint32_t qbase = sb + (w * 32 + 2 * t) * 128 + hsel * 8;
        mbar_wait(full + 8);
#pragma unroll
        for (int i = 0; i < 4; i++) xw[i] = fu(lds32f(sb + OFF_OB + (g >> 1) * 896 + (cta & 1) * 448 + w * 64 + t * 4 + i * 16));
        float c0[4] = {0.f, 0.f, 0.f, 0.f}, c1[4] = {0.f, 0.f, 0.f, 0.f};
#pragma unroll
        for (int i = 0; i < 4; i++) {
            const uint32_t r0 = qbase + i * 1024 + ((g ^ (2 * t)) << 4), r1 = qbase + i * 1024 + 128 + ((g ^ (2 * t + 1)) << 4);
            const uint2 a0 = lds64(r0), a1 = lds64(r1), a2 = lds64(r0 ^ 8), a3 = lds64(r1 ^ 8);
            const uint32_t b0 = prmt(xw[i], sel0), b1 = prmt(xw[i], sel1);
            mma16816(c0, a0.x, a0.y, a1.x, a1.y, b0, b1);
            mma16816(c1, a2.x, a2.y, a3.x, a3.y, b0, b1);
        }
        slot_release(empty + 8 * (w >> 2), fu(c0[0]) ^ fu(c1[0]), zero, lane);
        const uint32_t qr = sb + OFF_QRED + w * 1024 + lane * 16;
        sts128f(qr + hsel * 512, c0[0], c0[1], c0[2], c0[3]);
        sts128f(qr + (hsel ^ 1) * 512, c1[0], c1[1], c1[2], c1[3]);
    } else {
        if (lane == 0) {
#pragma unroll
            for (int i = 3; i < 28; i++) mbar_init(full + 8 * i, 1);
#pragma unroll
            for (int i = 0; i < 14; i++) mbar_init(empty + 8 * i, i == 1 ? 3 : (i < 12 ? 4 : 8));
#pragma unroll
            for (int i = 0; i < 7; i++) mbar_init(qbar + 8 * i, 1);
            mbar_expect_tx(qbar, 4096);
            mbar_expect_tx(stbar, 64);
            mbar_expect_tx(obar, 2048);
#pragma unroll
            for (int i = 0; i < 4; i++) mbar_expect_tx(hbar + 8 * i, 512);
            fence_mbar_init();
        }
        __syncwarp();
        cluster_arrive();
        cluster_wait();
        SKEL_EXIT();
    }
    TS(0);
    bar_sync(1, 256);
    uint4 wa[8];
    {
        const int pk = j >> 2, lp = pk & 31, hf = pk >> 5;
        const uint32_t qa = sb + OFF_QRED + pk * 16;
        float4 a = lds128f(qa);
#pragma unroll
        for (int ww = 1; ww < 7; ww++) {
            const float4 v = lds128f(qa + ww * 1024);
            a.x += v.x; a.y += v.y; a.z += v.z; a.w += v.w;
        }
        const uint32_t dst = (lp & 3) * 4 + (j & 3);
        st_async128(mapa(sb + OFF_QBUF + ((r & 1) * 512 + (r >> 1) * 64 + (lp >> 2) * 8 + hf * 4) * 4, dst),
                    fu(a.x), fu(a.y), fu(a.z), fu(a.w), mapa(qbar, dst));
        {
            const int sw = 2 + (w >> 2);
            uint32_t dep = 0;
            mbar_wait(full + 8 * sw);
            if (proj) {
                const uint32_t rr = (lane & 6) + 8 * (lane & 1) + 16 * (lane >> 4);
                const uint32_t ck = (w & 3) * 2 + ((lane >> 3) & 1);
#pragma unroll
                for (int m = 0; m < 8; m++)
                    wa[m] = ldsm4t(sb + sw * SLOT + ((m >> 1) * 32 + (m & 1) + rr) * 128 + ((ck ^ ((lane & 6) + (m & 1))) << 4));
#pragma unroll
                for (int m = 0; m < 8; m++) dep ^= wa[m].x;
            }
            slot_release(empty + 8 * sw, dep, zero, lane);
            TS(4);
        }
        mbar_wait(qbar);
        const float2 u = lds64f(sb + OFF_QBUF + j * 8), v = lds64f(sb + OFF_QBUF + 2048 + j * 8);
        sts32(sb + OFF_QS + ((j >> 5) & 3) * 256 + (j & 1) * 128 + (j >> 7) * 64 + ((j >> 2) & 3) * 16 + ((j >> 4) & 1) * 8 + ((j >> 1) & 1) * 4,
              pack_bf16(u.x + v.x, u.y + v.y));
    }
    bar_sync(1, 256);
    TS(1);

    float s0 = 0.f, s1 = 0.f;
    {
        uint2 qf[8];
        const uint32_t qa = sb + OFF_QS + (g >> 2) * 128 + (g & 1) * 64 + t * 16;
        const uint32_t qx = ((g >> 1) & 1) * 8;
#pragma unroll
        for (int i = 0; i < 8; i++) qf[i] = lds64(qa + (i >> 1) * 256 + (((i & 1) * 8) ^ qx));
        const uint32_t kx = (g & 1) * 64;
        const uint32_t krow = sb + ((w & 3) * 8 + g) * 512 + t * 16;
        const int src = (lane & 28) + (g & 1);
#pragma unroll 1
        for (int k = 0; k < 4; k++) {
            const int st = 4 + 2 * k + (w >> 2);
            const uint32_t ka = krow + (st >= NSLOT ? st - NSLOT : st) * SLOT;
            mbar_wait(full + 8 * st);
            float a0[4] = {0.f, 0.f, 0.f, 0.f}, a1[4] = {0.f, 0.f, 0.f, 0.f};
#pragma unroll
            for (int i = 0; i < 8; i += 2) {
                const uint4 r0 = lds128(ka + ((i * 64) ^ kx)), r1 = lds128(ka + (((i + 1) * 64) ^ kx));
                mma16816(a0, r0.x, r0.y, r0.z, r0.w, qf[i].x, qf[i].y);
                mma16816(a1, r1.x, r1.y, r1.z, r1.w, qf[i + 1].x, qf[i + 1].y);
            }
            const float e0 = __shfl_sync(0xffffffffu, a0[0] + a1[0], src) + __shfl_sync(0xffffffffu, a0[2] + a1[2], src + 2);
            const float e1 = __shfl_sync(0xffffffffu, a0[1] + a1[1], src) + __shfl_sync(0xffffffffu, a0[3] + a1[3], src + 2);
            slot_release(empty + 8 * st, fu(e0), zero, lane);
            if (t == k) { s0 = e0; s1 = e1; }
            if (k == 0) TS(2);
        }
    }
    float Mown;
    {
        const float kscale = 0.0625f * 1.4426950408889634f;
        s0 = round_bf16(s0) * kscale;
        s1 = round_bf16(s1) * kscale;
        float m0 = s0, m1 = s1;
#pragma unroll
        for (int o = 16; o > 0; o >>= 1) {
            m0 = fmaxf(m0, __shfl_xor_sync(0xffffffffu, m0, o));
            m1 = fmaxf(m1, __shfl_xor_sync(0xffffffffu, m1, o));
        }
        if (lane < 2) sts32(sb + OFF_WST + (w * 2 + lane) * 4, fu(lane ? m1 : m0));
        bar_sync(1, 256);
        const float4 u0 = lds128f(sb + OFF_WST), u1 = lds128f(sb + OFF_WST + 16), u2 = lds128f(sb + OFF_WST + 32), u3 = lds128f(sb + OFF_WST + 48);
        const float M0 = fmaxf(fmaxf(fmaxf(u0.x, u0.z), fmaxf(u1.x, u1.z)), fmaxf(fmaxf(u2.x, u2.z), fmaxf(u3.x, u3.z)));
        const float M1 = fmaxf(fmaxf(fmaxf(u0.y, u0.w), fmaxf(u1.y, u1.w)), fmaxf(fmaxf(u2.y, u2.w), fmaxf(u3.y, u3.w)));
        Mown = (t & 1) ? M1 : M0;
        const uint32_t p = pack_bf16(ex2(s0 - M0), ex2(s1 - M1));
        const uint32_t pa = sb + OFF_PS + (4 * t + (w >> 1)) * 64 + (g >> 1) * 8 + (w & 1) * 4 + (g & 1) * 2;
        sts16(pa, (unsigned short)(p & 0xFFFFu));
        sts16(pa + 32, (unsigned short)(p >> 16));
        float l0 = __uint_as_float(p << 16), l1 = __uint_as_float(p & 0xFFFF0000u);
#pragma unroll
        for (int o = 16; o > 0; o >>= 1) {
            l0 += __shfl_xor_sync(0xffffffffu, l0, o);
            l1 += __shfl_xor_sync(0xffffffffu, l1, o);
        }
        if (lane < 2) sts32(sb + OFF_WST + 64 + (w * 2 + lane) * 4, fu(lane ? l1 : l0));
        bar_sync(1, 256);
        if (j < 4) {
            const float4 v0 = lds128f(sb + OFF_WST + 64), v1 = lds128f(sb + OFF_WST + 80), v2 = lds128f(sb + OFF_WST + 96), v3 = lds128f(sb + OFF_WST + 112);
            const float L0 = ((v0.x + v0.z) + (v1.x + v1.z)) + ((v2.x + v2.z) + (v3.x + v3.z));
            const float L1 = ((v0.y + v0.w) + (v1.y + v1.w)) + ((v2.y + v2.w) + (v3.y + v3.w));
            st_async128(mapa(sb + OFF_WST + 128 + s * 16, b * 4 + j), fu(M0), fu(L0), fu(M1), fu(L1), mapa(stbar, b * 4 + j));
        }
    }
    TS(3);

    const uint32_t h1_dst = pin(mapa(sb + OFF_HOP + r * 128 + g * 16 + (t >> 1) * 8, (t & 1) * 8 + w));
    const uint32_t h1_bar = pin(mapa(hbar + 8 * b, (t & 1) * 8 + w));
    const uint32_t h2_grp = (w >> 2) * 4 + (lane >> 3);
    const uint32_t h2_rank = h2_grp < 7 ? (r >> 3) * 7 + h2_grp : 14 + (r >> 3);
    const uint32_t h2_dst = pin(mapa(sb + OFF_OB + (w & 3) * OB_STRIDE + (r & 7) * 64 + (lane & 7) * 8, h2_rank));
    const uint32_t h2_bar = pin(mapa(obar, h2_rank));
    const uint32_t h2_src = pin(sb + OFF_HOP + (w & 3) * 512 + (lane & 7) * 16);
    const uint32_t h2_wait = pin(hbar + 8 * (w & 3));
    const uint32_t bars = pin(obar);
    const uint32_t ob_src = pin(sb + OFF_OB + (g & 3) * OB_STRIDE + (w >> 2) * 256 + (g >> 2) * 128 + t * 16);
    const uint32_t red_st = pin(sb + (w >> 2) * 2048 + (t >> 1) * 1024 + (w & 3) * 256 + g * 32 + (((t & 1) ^ (g >> 2)) * 16));
    const uint32_t red_ld = pin(sb + (w >> 1) * 256 + (lane & 7) * 32 + (((w & 1) ^ ((lane >> 2) & 1)) * 16) + ((lane >> 3) & 1) * 8 + (lane >> 4) * 4);
    unsigned long long* acc_p = pin_ptr(acc + ACC_IDX(c, j));
    __nv_bfloat16* out_p = pin_ptr(out + (2 * (w & 1) + (lane >> 4)) * 448 + c * 64 + (w >> 1) * 16 + (lane & 15));
    const uint32_t k_one = pin(zero + 1u);
    const bool h1_hi = pin(t >> 1) != 0, proj_on = pin(proj ? 1u : 0u) != 0;

    float acc0[4] = {0.f, 0.f, 0.f, 0.f}, acc1[4] = {0.f, 0.f, 0.f, 0.f};
    float wgt = 0.f;
    {
        const uint32_t voff = sb + (w >> 1) * 2048 + ((lane >> 4) * 8 + (lane & 7)) * 128;
        const uint32_t va0 = pin(voff + ((((w & 1) * 4 + ((lane >> 3) & 1)) ^ (lane & 7)) << 4));
        const uint32_t va1 = pin(va0 ^ 32);
        const uint32_t pa = pin(sb + OFF_PS + ((g >> 1) & 1) * 32 + t * 8);
        const uint32_t vb = bars - (obar - vfull);
#pragma unroll
        for (int k = 0; k < 4; k++) {
            const uint2 pw = lds64(pa + k * 64);
            mbar_wait_t(vb + 8 * k);
            const uint4 f0 = ldsm4t(va0 + k * 8192), f1 = ldsm4t(va1 + k * 8192);
            mma16816(acc0, f0.x, f0.y, f0.z, f0.w, pw.x, pw.y);
            mma16816(acc1, f1.x, f1.y, f1.z, f1.w, pw.x, pw.y);
            if (k & 1) slot_release(empty + 8 * (12 + (k >> 1)), fu(acc0[0]) ^ fu(acc1[0]), zero, lane);
        }
        uint2 pw[12];
#pragma unroll
        for (int k = 4; k < 16; k++) pw[k - 4] = lds64(pa + k * 64);
        {
            mbar_wait(stbar);
            const uint32_t sa = sb + OFF_WST + 128 + (t & 1) * 8;
            const float2 z0 = lds64f(sa), z1 = lds64f(sa + 16), z2 = lds64f(sa + 32), z3 = lds64f(sa + 48);
            const float mx = fmaxf(fmaxf(z0.x, z1.x), fmaxf(z2.x, z3.x));
            const float W = (ex2(z0.x - mx) * z0.y + ex2(z1.x - mx) * z1.y) + (ex2(z2.x - mx) * z2.y + ex2(z3.x - mx) * z3.y);
            wgt = __uint_as_float(pin(fu(__fdividef(ex2(Mown - mx), W))));
        }
        bool ok = mbar_try(vb + 32);
        uint4 f0, f1;
#pragma unroll
        for (int k = 4; k < 16; k++) {
            const uint32_t so = (k < 12 ? k : k - 12) * 8192;
            if (!ok) mbar_wait_t(vb + 8 * k);
            if (k == 15) { TC(16); GT_AT(1); }
            const uint4 n0 = ldsm4t(va0 + so), n1 = ldsm4t(va1 + so);
            if (k < 15) ok = mbar_try(vb + 8 * k + 8);
            if (k > 4) {
                mma16816(acc0, f0.x, f0.y, f0.z, f0.w, pw[k - 5].x, pw[k - 5].y);
                mma16816(acc1, f1.x, f1.y, f1.z, f1.w, pw[k - 5].x, pw[k - 5].y);
            }
            f0 = n0; f1 = n1;
        }
        mma16816(acc0, f0.x, f0.y, f0.z, f0.w, pw[11].x, pw[11].y);
        mma16816(acc1, f1.x, f1.y, f1.z, f1.w, pw[11].x, pw[11].y);
    }
    st_async64(h1_dst, fu((h1_hi ? acc1[0] : acc0[0]) * wgt), fu((h1_hi ? acc1[2] : acc0[2]) * wgt), h1_bar);
    { TC(17); GT_AT(2); }
    {
        mbar_wait_t(h2_wait);
        { TC(18); GT_AT(3); }
        const float4 v0 = lds128f(h2_src), v1 = lds128f(h2_src + 128), v2 = lds128f(h2_src + 256), v3 = lds128f(h2_src + 384);
        st_async64(h2_dst, pack_bf16((v0.x + v1.x) + (v2.x + v3.x), (v0.y + v1.y) + (v2.y + v3.y)),
                      pack_bf16((v0.z + v1.z) + (v2.z + v3.z), (v0.w + v1.w) + (v2.w + v3.w)), h2_bar);
    }
    { TC(19); GT_AT(4); }
    mbar_wait_t(bars);
    if (proj_on) {
        { TC(20); GT_AT(5); }
        const uint4 oa = lds128(ob_src), ob = lds128(ob_src + 64);
        float x0[4] = {0.f, 0.f, 0.f, 0.f}, x1[4] = {0.f, 0.f, 0.f, 0.f}, y0[4] = {0.f, 0.f, 0.f, 0.f}, y1[4] = {0.f, 0.f, 0.f, 0.f};
        mma16816(x0, wa[0].x, wa[0].y, wa[0].z, wa[0].w, oa.x, oa.y);
        mma16816(y0, wa[4].x, wa[4].y, wa[4].z, wa[4].w, oa.x, oa.y);
        mma16816(x1, wa[1].x, wa[1].y, wa[1].z, wa[1].w, oa.z, oa.w);
        mma16816(y1, wa[5].x, wa[5].y, wa[5].z, wa[5].w, oa.z, oa.w);
        mma16816(x0, wa[2].x, wa[2].y, wa[2].z, wa[2].w, ob.x, ob.y);
        mma16816(y0, wa[6].x, wa[6].y, wa[6].z, wa[6].w, ob.x, ob.y);
        mma16816(x1, wa[3].x, wa[3].y, wa[3].z, wa[3].w, ob.z, ob.w);
        mma16816(y1, wa[7].x, wa[7].y, wa[7].z, wa[7].w, ob.z, ob.w);
        float z[4];
#pragma unroll
        for (int i = 0; i < 4; i++) {
            z[i] = x0[i] + x1[i];
            if (h1_hi) z[i] = y0[i] + y1[i];
        }
        sts128f(red_st, z[0], z[1], z[2], z[3]);
        { TC(21); GT_AT(6); }
        bar_sync(1, 256);
        const float sum = (lds32f(red_ld) + lds32f(red_ld + 1024)) + (lds32f(red_ld + 2048) + lds32f(red_ld + 3072));
        const uint32_t bits = fu(sum);
        const uint32_t sh = 129u - ((bits >> 23) & 0xFFu);
        const uint32_t smant = (((bits << 3) & 0x3FFFFF8u) | 0x4000000u) ^ (uint32_t)((int)bits >> 31);
        long long fx;
        asm("shr.s64 %0, %1, %2;" : "=l"(fx) : "l"((long long)((unsigned long long)smant << 32)), "r"(sh));
        const uint32_t ilo = ((uint32_t)fx & ~0x3FFu) | k_one;
        const unsigned long long inc = ((unsigned long long)fx & 0xFFFFFFFF00000000ull) | ilo;
        const bool fast = __any_sync(0xffffffffu, fabsf(sum) >= 0x1p-30f) && fabsf(sum) < 8.0f;
        { TC(22); GT_AT(7); }
        unsigned long long tot = 0ull;
        asm volatile("{\n.reg .pred p;\nsetp.ne.u32 p, %3, 0;\n@p atom.relaxed.gpu.global.add.u64 %0, [%1], %2;\n}"
                     : "+l"(tot) : "l"(acc_p), "l"(inc), "r"((uint32_t)fast) : "memory");
        if (!fast) { accumulate_slow(sum, acc_p, out_p); return; }
        tot += inc;
        const uint32_t cnt = (uint32_t)tot & 0x3FFu;
        asm volatile("{\n.reg .pred p;\nsetp.eq.u32 p, %3, 16;\n@p st.global.u16 [%0], %1;\n@p st.global.u64 [%2], 0;\n}"
                     ::"l"(out_p), "h"(__bfloat16_as_ushort(__float2bfloat16(acc_value(tot)))), "l"(acc_p), "r"(cnt) : "memory");
        if (cnt > 16u) finish_with_side(tot, acc_p, out_p);
        TC(23);
        TS(9);
    }
    GT_END();
    TC_DUMP();
    PROF_DUMP();
}

typedef CUresult (*EncodeFn)(CUtensorMap*, CUtensorMapDataType, cuuint32_t, void*, const cuuint64_t*, const cuuint64_t*,
                             const cuuint32_t*, const cuuint32_t*, CUtensorMapInterleave, CUtensorMapSwizzle,
                             CUtensorMapL2promotion, CUtensorMapFloatOOBfill);

}

extern "C" void kernel_launch(void* const* d_in, const int* in_sizes, int n_in, void* d_out, int out_size) {
    (void)in_sizes; (void)n_in; (void)out_size;
    static EncodeFn encode = nullptr;
    static void* acc = nullptr;
    if (!encode) {
        cudaDriverEntryPointQueryResult qr;
        cudaGetDriverEntryPoint("cuTensorMapEncodeTiled", (void**)&encode, cudaEnableDefault, &qr);
        cudaGetSymbolAddress(&acc, g_acc);
        cudaFuncSetAttribute(decode_kernel, cudaFuncAttributeMaxDynamicSharedMemorySize, SMEM_BYTES);
        cudaFuncSetAttribute(decode_kernel, cudaFuncAttributeNonPortableClusterSizeAllowed, 1);
    }
    CUtensorMap wo_map;
    const cuuint64_t gdim[2] = {448, 4096};
    const cuuint64_t gstr[1] = {896};
    const cuuint32_t box[2] = {64, 128};
    const cuuint32_t estr[2] = {1, 1};
    encode(&wo_map, CU_TENSOR_MAP_DATA_TYPE_BFLOAT16, 2, d_in[4], gdim, gstr, box, estr, CU_TENSOR_MAP_INTERLEAVE_NONE,
           CU_TENSOR_MAP_SWIZZLE_128B, CU_TENSOR_MAP_L2_PROMOTION_NONE, CU_TENSOR_MAP_FLOAT_OOB_FILL_NONE);

    CUtensorMap wq_map;
    const cuuint64_t qdim[2] = {4096, 448};
    const cuuint64_t qstr[1] = {8192};
    const cuuint32_t qbox[2] = {64, 224};
    encode(&wq_map, CU_TENSOR_MAP_DATA_TYPE_BFLOAT16, 2, d_in[3], qdim, qstr, qbox, estr, CU_TENSOR_MAP_INTERLEAVE_NONE,
           CU_TENSOR_MAP_SWIZZLE_128B, CU_TENSOR_MAP_L2_PROMOTION_NONE, CU_TENSOR_MAP_FLOAT_OOB_FILL_NONE);
    CUtensorMap v_map;
    const cuuint64_t vdim[3] = {64, 4ull * 8 * SK, 4};
    const cuuint64_t vstr[2] = {512, 128};
    const cuuint32_t vbox[3] = {64, 16, 4};
    const cuuint32_t vestr[3] = {1, 1, 1};
    encode(&v_map, CU_TENSOR_MAP_DATA_TYPE_BFLOAT16, 3, d_in[2], vdim, vstr, vbox, vestr, CU_TENSOR_MAP_INTERLEAVE_NONE,
           CU_TENSOR_MAP_SWIZZLE_128B, (CUtensorMapL2promotion)VPROMO, CU_TENSOR_MAP_FLOAT_OOB_FILL_NONE);

    cudaLaunchConfig_t cfg = {};
    cfg.gridDim = dim3(128);
    cfg.blockDim = dim3(NTHREADS);
    cfg.dynamicSmemBytes = SMEM_BYTES;
    cfg.stream = cudaStreamPerThread;
    cudaLaunchAttribute attr[2];
    attr[0].id = cudaLaunchAttributeClusterDimension;
    attr[0].val.clusterDim.x = CLDIM; attr[0].val.clusterDim.y = 1; attr[0].val.clusterDim.z = 1;
    attr[1].id = cudaLaunchAttributeClusterSchedulingPolicyPreference;
    attr[1].val.clusterSchedulingPolicyPreference = cudaClusterSchedulingPolicyLoadBalancing;
    cfg.attrs = attr;
    cfg.numAttrs = 2;
    cudaLaunchKernelEx(&cfg, decode_kernel, (const __nv_bfloat16*)d_in[0], (const __nv_bfloat16*)d_in[1], (const __nv_bfloat16*)d_in[3],
                       (__nv_bfloat16*)d_out, (unsigned long long*)acc, 0u, wq_map, wo_map, v_map);
}
```

```cpp
#include <cuda_runtime.h>
#include <cuda_bf16.h>
#include <cuda.h>
#include <stdint.h>

namespace {

constexpr int SK = 4096, WIN0 = 3072;
constexpr int SLOT = 16384;
constexpr int OFF_BAR  = 6 * SLOT;
constexpr int OFF_QBUF = OFF_BAR + 416;
constexpr int OFF_QS   = OFF_QBUF + 4096;
constexpr int OFF_WST  = OFF_QS + 1024;
constexpr int OB_STRIDE = 576;
constexpr int OFF_OB   = OFF_WST + 192;
constexpr int OFF_HOP  = OFF_OB + 4 * OB_STRIDE;
constexpr int OFF_QRED = OFF_HOP + 2048;
constexpr int OFF_PS   = OFF_QRED;
constexpr int SMEM_BYTES = OFF_QRED + 7 * 1024;
static_assert(SMEM_BYTES <= 115712, "two CTAs must fit on one SM");
constexpr int NTHREADS = 288;
constexpr int SPIN_LIMIT = 1 << 20;

#define TK0 500
#define TDV 331
#define TGAP 0
#define TDO 250
#define T7 1600
#define WLK 2
#define WLV 4
#define PRE 3
#define STK 0
#define STV 0
#define STO 0
#define TDK (2 * TDV)
#define WLO 1

constexpr int ACC_WORDS = 1792 * 2;
__device__ __align__(1024) unsigned long long g_acc[ACC_WORDS];
__device__ float g_side[ACC_WORDS];

#define GT_AT(n)
#define GT_END()

__device__ __forceinline__ void mbar_init(uint32_t bar, uint32_t cnt) {
    asm volatile("mbarrier.init.shared::cta.b64 [%0], %1;" ::"r"(bar), "r"(cnt) : "memory");
}
__device__ __forceinline__ void mbar_expect_tx(uint32_t bar, uint32_t bytes) {
    asm volatile("mbarrier.arrive.expect_tx.shared::cta.b64 _, [%0], %1;" ::"r"(bar), "r"(bytes) : "memory");
}
__device__ __forceinline__ void slot_release(uint32_t bar, uint32_t dep, uint32_t zero, int lane) {
    if (lane == 0) asm volatile("mbarrier.arrive.shared::cta.b64 _, [%0];" ::"r"(bar + (dep & zero)) : "memory");
}
__device__ __forceinline__ void mbar_wait_n(uint32_t bar, uint32_t& n) {
    asm volatile("{\n.reg .pred p, q;\n"
                 "WAIT_LOOP:\n"
                 "mbarrier.try_wait.parity.shared::cta.b64 p, [%1], 0;\n"
                 "add.u32 %0, %0, 1;\n"
                 "setp.lt.and.u32 q, %0, %2, !p;\n"
                 "@q bra.uni WAIT_LOOP;\n}"
                 : "+r"(n) : "r"(bar), "n"(SPIN_LIMIT) : "memory");
}
#define mbar_wait(bar) mbar_wait_n(bar, spins)
__device__ __forceinline__ void mbar_wait_fast(uint32_t bar) {
    asm volatile("{\n.reg .pred p;\nWAIT_LOOP:\nmbarrier.try_wait.parity.shared::cta.b64 p, [%0], 0;\n@!p bra.uni WAIT_LOOP;\n}"
                 ::"r"(bar) : "memory");
}
__device__ __forceinline__ uint32_t now_ns() {
    uint32_t t;
    asm volatile("mov.u32 %0, %%globaltimer_lo;" : "=r"(t)::"memory");
    return t;
}
__device__ __forceinline__ void pace(uint32_t due, uint32_t bar) {
    while ((int)(now_ns() - due) < 0) {
        uint32_t ok;
        asm volatile("{\n.reg .pred p;\nmbarrier.test_wait.parity.shared::cta.b64 p, [%1], 0;\nselp.u32 %0, 1, 0, p;\n}"
                     : "=r"(ok) : "r"(bar) : "memory");
        if (ok) break;
    }
}
__device__ __forceinline__ void bulk_g2s(uint32_t dst, const void* src, uint32_t bytes, uint32_t bar) {
    asm volatile("cp.async.bulk.shared::cluster.global.mbarrier::complete_tx::bytes [%0], [%1], %2, [%3];"
                 ::"r"(dst), "l"(src), "r"(bytes), "r"(bar) : "memory");
}
__device__ __forceinline__ void bulk_g2s_mc(uint32_t dst, const void* src, uint32_t bytes, uint32_t bar, uint16_t mask) {
    asm volatile("cp.async.bulk.shared::cluster.global.mbarrier::complete_tx::bytes.multicast::cluster [%0], [%1], %2, [%3], %4;"
                 ::"r"(dst), "l"(src), "r"(bytes), "r"(bar), "h"(mask) : "memory");
}
__device__ __forceinline__ void tma2d(uint32_t dst, const CUtensorMap* tm, int c0, int c1, uint32_t bar) {
    asm volatile("cp.async.bulk.tensor.2d.shared::cluster.global.mbarrier::complete_tx::bytes [%0], [%1, {%3, %4}], [%2];"
                 ::"r"(dst), "l"(tm), "r"(bar), "r"(c0), "r"(c1) : "memory");
}
__device__ __forceinline__ void tma3d(uint32_t dst, const CUtensorMap* tm, int c1, uint32_t bar) {
    asm volatile("cp.async.bulk.tensor.3d.shared::cluster.global.mbarrier::complete_tx::bytes [%0], [%1, {%3, %4, %3}], [%2];"
                 ::"r"(dst), "l"(tm), "r"(bar), "r"(0), "r"(c1) : "memory");
}
__device__ __forceinline__ uint32_t pin(uint32_t v) {
    uint32_t o;
    asm volatile("shfl.sync.bfly.b32 %0, %1, 0, 0x1f, 0xffffffff;" : "=r"(o) : "r"(v));
    return o;
}
template <typename T> __device__ __forceinline__ T* pin_ptr(T* p) {
    const unsigned long long a = (unsigned long long)p;
    return (T*)(((unsigned long long)pin((uint32_t)(a >> 32)) << 32) | pin((uint32_t)a));
}
__device__ __forceinline__ bool elect_one() {
    uint32_t p;
    asm volatile("{\n.reg .pred P;\nelect.sync _|P, 0xffffffff;\nselp.u32 %0, 1, 0, P;\n}" : "=r"(p));
    return p != 0;
}
__device__ __forceinline__ void bar_compute() { asm volatile("bar.sync 1, 256;" ::: "memory"); }
__device__ __forceinline__ void cluster_arrive() { asm volatile("barrier.cluster.arrive.relaxed.aligned;" ::: "memory"); }
__device__ __forceinline__ void cluster_wait() { asm volatile("barrier.cluster.wait.aligned;" ::: "memory"); }
__device__ __forceinline__ void fence_mbar_init() { asm volatile("fence.mbarrier_init.release.cluster;" ::: "memory"); }
__device__ __forceinline__ uint32_t mapa(uint32_t a, uint32_t rank) {
    uint32_t o;
    asm("mapa.shared::cluster.u32 %0, %1, %2;" : "=r"(o) : "r"(a), "r"(rank));
    return o;
}
__device__ __forceinline__ void st_async128(uint32_t a, uint32_t x, uint32_t y, uint32_t z, uint32_t w, uint32_t bar) {
    asm volatile("st.async.shared::cluster.mbarrier::complete_tx::bytes.v4.b32 [%0], {%1,%2,%3,%4}, [%5];"
                 ::"r"(a), "r"(x), "r"(y), "r"(z), "r"(w), "r"(bar) : "memory");
}
__device__ __forceinline__ void st_async64(uint32_t a, uint32_t x, uint32_t y, uint32_t bar) {
    asm volatile("st.async.shared::cluster.mbarrier::complete_tx::bytes.v2.b32 [%0], {%1,%2}, [%3];"
                 ::"r"(a), "r"(x), "r"(y), "r"(bar) : "memory");
}
__device__ __forceinline__ void mma16816(float (&c)[4], const uint4& a, uint32_t b0, uint32_t b1) {
    asm volatile("mma.sync.aligned.m16n8k16.row.col.f32.bf16.bf16.f32 {%0,%1,%2,%3}, {%4,%5,%6,%7}, {%8,%9}, {%0,%1,%2,%3};"
                 : "+f"(c[0]), "+f"(c[1]), "+f"(c[2]), "+f"(c[3])
                 : "r"(a.x), "r"(a.y), "r"(a.z), "r"(a.w), "r"(b0), "r"(b1));
}
__device__ __forceinline__ uint4 lds128(uint32_t a) {
    uint4 v;
    asm volatile("ld.shared.v4.u32 {%0,%1,%2,%3}, [%4];" : "=r"(v.x), "=r"(v.y), "=r"(v.z), "=r"(v.w) : "r"(a) : "memory");
    return v;
}
__device__ __forceinline__ float4 lds128f(uint32_t a) {
    float4 v;
    asm volatile("ld.shared.v4.f32 {%0,%1,%2,%3}, [%4];" : "=f"(v.x), "=f"(v.y), "=f"(v.z), "=f"(v.w) : "r"(a) : "memory");
    return v;
}
__device__ __forceinline__ float2 lds64f(uint32_t a) {
    float2 v;
    asm volatile("ld.shared.v2.f32 {%0,%1}, [%2];" : "=f"(v.x), "=f"(v.y) : "r"(a) : "memory");
    return v;
}
__device__ __forceinline__ uint2 lds64(uint32_t a) {
    uint2 v;
    asm volatile("ld.shared.v2.u32 {%0,%1}, [%2];" : "=r"(v.x), "=r"(v.y) : "r"(a) : "memory");
    return v;
}
__device__ __forceinline__ uint32_t lds32(uint32_t a) {
    uint32_t v;
    asm volatile("ld.shared.u32 %0, [%1];" : "=r"(v) : "r"(a) : "memory");
    return v;
}
__device__ __forceinline__ float lds32f(uint32_t a) { return __uint_as_float(lds32(a)); }
__device__ __forceinline__ void sts128f(uint32_t a, float x, float y, float z, float w) {
    asm volatile("st.shared.v4.f32 [%0], {%1,%2,%3,%4};" ::"r"(a), "f"(x), "f"(y), "f"(z), "f"(w) : "memory");
}
__device__ __forceinline__ void sts32(uint32_t a, uint32_t v) {
    asm volatile("st.shared.u32 [%0], %1;" ::"r"(a), "r"(v) : "memory");
}
__device__ __forceinline__ void sts16(uint32_t a, unsigned short v) {
    asm volatile("st.shared.u16 [%0], %1;" ::"r"(a), "h"(v) : "memory");
}
__device__ __forceinline__ uint4 ldsm4t(uint32_t a) {
    uint4 v;
    asm volatile("ldmatrix.sync.aligned.m8n8.x4.trans.shared.b16 {%0,%1,%2,%3}, [%4];"
                 : "=r"(v.x), "=r"(v.y), "=r"(v.z), "=r"(v.w) : "r"(a) : "memory");
    return v;
}
__device__ __forceinline__ uint32_t pack_bf16(float lo, float hi) {
    uint32_t r;
    asm("cvt.rn.bf16x2.f32 %0, %1, %2;" : "=r"(r) : "f"(hi), "f"(lo));
    return r;
}
__device__ __forceinline__ float round_bf16(float v) { return __uint_as_float(pack_bf16(0.f, v) & 0xFFFF0000u); }
__device__ __forceinline__ float ex2(float x) {
    float y;
    asm("ex2.approx.ftz.f32 %0, %1;" : "=f"(y) : "f"(x));
    return y;
}
__device__ __forceinline__ uint32_t fu(float v) { return __float_as_uint(v); }

__device__ __forceinline__ float acc_value(unsigned long long tot) {
    return fmaf((float)(int)(uint32_t)(tot >> 32), 0x1p-24f, (float)((uint32_t)tot >> 10) * 0x1p-46f);
}
__device__ __noinline__ void finish_with_side(unsigned long long tot, unsigned long long* acc_p, __nv_bfloat16* out_p) {
    if ((tot & 31ull) != 16ull) return;
    __threadfence();
    const float side = atomicExch(&g_side[acc_p - g_acc], 0.0f);
    *out_p = __float2bfloat16(acc_value(tot) + side);
    *acc_p = 0ull;
}
__device__ __noinline__ void accumulate_slow(float sum, unsigned long long* acc_p, __nv_bfloat16* out_p) {
    atomicAdd(&g_side[acc_p - g_acc], sum);
    __threadfence();
    finish_with_side(atomicAdd(acc_p, 33ull) + 33ull, acc_p, out_p);
}

__global__ void __launch_bounds__(NTHREADS, 2)
decode_kernel(const __nv_bfloat16* __restrict__ x, const __nv_bfloat16* __restrict__ kc,
              const __nv_bfloat16* __restrict__ wq, __nv_bfloat16* __restrict__ out,
              unsigned long long* __restrict__ acc, const uint32_t zero,
              const __grid_constant__ CUtensorMap wq_map, const __grid_constant__ CUtensorMap wo_map,
              const __grid_constant__ CUtensorMap v_map) {
    asm volatile("prefetch.global.L2 [%0];" ::"l"((const char*)wq + (blockIdx.x * 224 + min(threadIdx.x, 223u)) * 128));

    extern __shared__ __align__(1024) unsigned char smem[];
    const uint32_t sb = (uint32_t)__cvta_generic_to_shared(smem);
    const int warp = threadIdx.x >> 5, lane = threadIdx.x & 31;
    const int cta = blockIdx.x;
    const int gk = cta >> 4, r = cta & 15, b = r >> 2, s = r & 3;
    const bool proj = r < 14;
    const int c = r - 7 * (r >= 7);
    const uint32_t qfull = sb + OFF_BAR, kfull = qfull + 8, vfull = kfull + 64, ofull = vfull + 128, empty = ofull + 32;
    const uint32_t qbar = empty + 14 * 8, stbar = qbar + 8, obar = qbar + 16, hbar = qbar + 24;
    uint32_t spins = 0;

    if (warp == 0) {
        const bool leader = elect_one();
        if (leader) {
            mbar_init(qfull, 1);
            mbar_expect_tx(qfull, 28672 + 3584);
            tma2d(sb, &wq_map, (cta >> 1) * 64, (cta & 1) * 224, qfull);
            fence_mbar_init();
        }
        uint32_t due = now_ns() + TK0 - (gk == 7 ? T7 : 0) + (r - 8) * STK;
        __syncwarp();
        cluster_arrive();
        cluster_wait();
        if (leader) {
            if (proj) bulk_g2s_mc(sb + OFF_OB + r * 256, (const char*)x + r * 256, 256, qfull, (uint16_t)0xFFFF);
            int row = (b * 8 + gk) * SK + WIN0 + s * 256;
            const char* kp = (const char*)kc + (size_t)row * 512;
            uint32_t bar = kfull, dst = sb + 2 * SLOT;
#pragma unroll 1
            for (int i = 0; i < 8; i++) {
                mbar_expect_tx(bar, 16384);
                if (i >= 4) mbar_wait(empty + 8 * (i - 4));
                pace(due, i < WLK ? qfull : bar - 8 * WLK);
                bulk_g2s(dst, kp, 16384, bar);
                if (i == 1) {
                    asm volatile("prefetch.tensormap [%0];" ::"l"(&v_map) : "memory");
                    asm volatile("prefetch.tensormap [%0];" ::"l"(&wo_map) : "memory");
                }
                due += TDK;
                kp += 16384;
                bar += 8;
                dst = (i == 3) ? sb : dst + SLOT;
            }
            due += (r - 8) * (STV - STK);
#pragma unroll 1
            for (int k = 0; k < 16; k++) {
                mbar_expect_tx(bar, 8192);
                mbar_wait(empty + 8 * (4 + (k >> 1)));
                const int d = k - WLV;
                pace(due, vfull + 8 * (d < 0 ? (d >> 1) : d));
                tma3d(dst, &v_map, row, bar);
                due += TDV;
                row += 16;
                bar += 8;
                dst = (k == 3) ? sb : dst + 8192;
            }
            if (proj) {
                due += TGAP + (r - 8) * (STO - STV);
                mbar_wait(empty + 8 * 12);
                mbar_wait(empty + 8 * 13);
#pragma unroll 1
                for (int n = 0; n < 4; n++) {
                    mbar_expect_tx(bar, 8192);
                    pace(due, bar - 8 * WLO);
                    tma2d(sb + n * 8192, &wo_map, c * 64, (2 * gk + (r >= 7)) * 256 + n * 64, bar);
                    due += TDO;
                    bar += 8;
                }
            }
        }
        return;
    }

    const int w = warp - 1, j = threadIdx.x - 32;
    const int g = lane >> 2, t = lane & 3;

    if (w < 7) {
        cluster_arrive();
        cluster_wait();
        const uint32_t qa = sb + (w * 32 + (lane >> 4) * 8 + (lane & 7)) * 128;
        const uint32_t xa = sb + OFF_OB + (g & 3) * 896 + (cta & 1) * 448 + w * 64 + t * 4;
        mbar_wait(qfull);
        const uint32_t x0 = lds32(xa), x1 = lds32(xa + 16), x2 = lds32(xa + 32), x3 = lds32(xa + 48);
        float cq[4][4];
#pragma unroll
        for (int m = 0; m < 4; m++) {
            const uint32_t a = qa + (((2 * m + ((lane >> 3) & 1)) ^ (lane & 7)) << 4);
            const uint4 f0 = ldsm4t(a), f1 = ldsm4t(a + 2048);
            cq[m][0] = cq[m][1] = cq[m][2] = cq[m][3] = 0.f;
            mma16816(cq[m], f0, x0, x1);
            mma16816(cq[m], f1, x2, x3);
        }
        slot_release(empty + 8 * (w >> 2), fu(cq[0][0]) ^ fu(cq[1][0]) ^ fu(cq[2][0]) ^ fu(cq[3][0]), zero, lane);
        const int hf = t >> 1;
        const uint32_t qr = sb + OFF_QRED + w * 1024 + (t & 1) * 512 + hf * 128 + g * 16;
        sts128f(qr, hf ? cq[0][2] : cq[0][0], hf ? cq[1][2] : cq[1][0], hf ? cq[2][2] : cq[2][0], hf ? cq[3][2] : cq[3][0]);
        sts128f(qr + 256, hf ? cq[0][3] : cq[0][1], hf ? cq[1][3] : cq[1][1], hf ? cq[2][3] : cq[2][1], hf ? cq[3][3] : cq[3][1]);
    } else {
        if (lane == 0) {
#pragma unroll
            for (int i = 0; i < 28; i++) mbar_init(kfull + 8 * i, 1);
#pragma unroll
            for (int i = 0; i < 14; i++) mbar_init(empty + 8 * i, i == 1 ? 3 : (i < 10 ? 4 : 8));
#pragma unroll
            for (int i = 0; i < 7; i++) mbar_init(qbar + 8 * i, 1);
            mbar_expect_tx(qbar, 4096);
            mbar_expect_tx(stbar, 64);
            mbar_expect_tx(obar, 2048);
#pragma unroll
            for (int i = 0; i < 4; i++) mbar_expect_tx(hbar + 8 * i, 512);
            fence_mbar_init();
        }
        __syncwarp();
        cluster_arrive();
        cluster_wait();
    }
    bar_compute();
    {
        const int pk = j >> 2;
        const uint32_t ra = sb + OFF_QRED + pk * 16;
        float4 a = lds128f(ra);
#pragma unroll
        for (int ww = 1; ww < 7; ww++) {
            const float4 v = lds128f(ra + ww * 1024);
            a.x += v.x; a.y += v.y; a.z += v.z; a.w += v.w;
        }
        const uint32_t dst = (pk >> 4) * 4 + (j & 3);
        st_async128(mapa(sb + OFF_QBUF + (r & 1) * 2048 + (r >> 1) * 256 + (pk & 15) * 16, dst),
                    fu(a.x), fu(a.y), fu(a.z), fu(a.w), mapa(qbar, dst));
        mbar_wait(qbar);
        const uint32_t qb = sb + OFF_QBUF + (j >> 5) * 256 + (j & 7) * 32 + ((j >> 3) & 3) * 4;
        const float q0 = lds32f(qb) + lds32f(qb + 2048), q1 = lds32f(qb + 16) + lds32f(qb + 2064);
        sts32(sb + OFF_QS + ((j >> 5) & 3) * 256 + (j & 1) * 128 + (j >> 7) * 64 + ((j >> 2) & 3) * 16 + ((j >> 4) & 1) * 8 + ((j >> 1) & 1) * 4,
              pack_bf16(q0, q1));
    }
    bar_compute();

    float s0 = 0.f, s1 = 0.f;
    {
        uint2 qf[8];
        const uint32_t qa = sb + OFF_QS + (g >> 2) * 128 + (g & 1) * 64 + t * 16;
        const uint32_t qx = ((g >> 1) & 1) * 8;
#pragma unroll
        for (int i = 0; i < 8; i++) qf[i] = lds64(qa + (i >> 1) * 256 + (((i & 1) * 8) ^ qx));
        const uint32_t kx = (g & 1) * 64;
        const uint32_t krow = sb + ((w & 3) * 8 + g) * 512 + t * 16;
        const int src = (lane & 28) + (g & 1);
#pragma unroll 1
        for (int k = 0; k < 4; k++) {
            const int ch = 2 * k + (w >> 2);
            const uint32_t ka = krow + (ch >= 4 ? ch - 4 : ch + 2) * SLOT;
            mbar_wait(kfull + 8 * ch);
            float a0[4] = {0.f, 0.f, 0.f, 0.f}, a1[4] = {0.f, 0.f, 0.f, 0.f};
#pragma unroll
            for (int i = 0; i < 8; i += 2) {
                const uint4 r0 = lds128(ka + ((i * 64) ^ kx)), r1 = lds128(ka + (((i + 1) * 64) ^ kx));
                mma16816(a0, r0, qf[i].x, qf[i].y);
                mma16816(a1, r1, qf[i + 1].x, qf[i + 1].y);
            }
            const float e0 = __shfl_sync(0xffffffffu, a0[0] + a1[0], src) + __shfl_sync(0xffffffffu, a0[2] + a1[2], src + 2);
            const float e1 = __shfl_sync(0xffffffffu, a0[1] + a1[1], src) + __shfl_sync(0xffffffffu, a0[3] + a1[3], src + 2);
            slot_release(empty + 8 * (2 + ch), fu(e0), zero, lane);
            if (t == k) { s0 = e0; s1 = e1; }
        }
    }
    float Mown;
    {
        const float kscale = 0.0625f * 1.4426950408889634f;
        s0 = round_bf16(s0) * kscale;
        s1 = round_bf16(s1) * kscale;
        float m0 = s0, m1 = s1;
#pragma unroll
        for (int o = 16; o > 0; o >>= 1) {
            m0 = fmaxf(m0, __shfl_xor_sync(0xffffffffu, m0, o));
            m1 = fmaxf(m1, __shfl_xor_sync(0xffffffffu, m1, o));
        }
        if (lane < 2) sts32(sb + OFF_WST + (w * 2 + lane) * 4, fu(lane ? m1 : m0));
        bar_compute();
        const float4 u0 = lds128f(sb + OFF_WST), u1 = lds128f(sb + OFF_WST + 16), u2 = lds128f(sb + OFF_WST + 32), u3 = lds128f(sb + OFF_WST + 48);
        const float M0 = fmaxf(fmaxf(fmaxf(u0.x, u0.z), fmaxf(u1.x, u1.z)), fmaxf(fmaxf(u2.x, u2.z), fmaxf(u3.x, u3.z)));
        const float M1 = fmaxf(fmaxf(fmaxf(u0.y, u0.w), fmaxf(u1.y, u1.w)), fmaxf(fmaxf(u2.y, u2.w), fmaxf(u3.y, u3.w)));
        Mown = (t & 1) ? M1 : M0;
        const uint32_t p = pack_bf16(ex2(s0 - M0), ex2(s1 - M1));
        const uint32_t pa = sb + OFF_PS + (4 * t + (w >> 1)) * 64 + (g >> 1) * 8 + (w & 1) * 4 + (g & 1) * 2;
        sts16(pa, (unsigned short)(p & 0xFFFFu));
        sts16(pa + 32, (unsigned short)(p >> 16));
        float l0 = __uint_as_float(p << 16), l1 = __uint_as_float(p & 0xFFFF0000u);
#pragma unroll
        for (int o = 16; o > 0; o >>= 1) {
            l0 += __shfl_xor_sync(0xffffffffu, l0, o);
            l1 += __shfl_xor_sync(0xffffffffu, l1, o);
        }
        if (lane < 2) sts32(sb + OFF_WST + 64 + (w * 2 + lane) * 4, fu(lane ? l1 : l0));
        bar_compute();
        if (j < 4) {
            const float4 v0 = lds128f(sb + OFF_WST + 64), v1 = lds128f(sb + OFF_WST + 80), v2 = lds128f(sb + OFF_WST + 96), v3 = lds128f(sb + OFF_WST + 112);
            const float L0 = ((v0.x + v0.z) + (v1.x + v1.z)) + ((v2.x + v2.z) + (v3.x + v3.z));
            const float L1 = ((v0.y + v0.w) + (v1.y + v1.w)) + ((v2.y + v2.w) + (v3.y + v3.w));
            st_async128(mapa(sb + OFF_WST + 128 + s * 16, b * 4 + j), fu(M0), fu(L0), fu(M1), fu(L1), mapa(stbar, b * 4 + j));
        }
    }

    const uint32_t h1_dst = pin(mapa(sb + OFF_HOP + r * 128 + (t >> 1) * 64 + g * 8, (t & 1) * 8 + w));
    const uint32_t h1_bar = pin(mapa(hbar + 8 * b, (t & 1) * 8 + w));
    const uint32_t h2_grp = (w >> 2) * 4 + (lane >> 3);
    const uint32_t h2_rank = h2_grp < 7 ? (r >> 3) * 7 + h2_grp : 14 + (r >> 3);
    const uint32_t h2_dst = pin(mapa(sb + OFF_OB + (w & 3) * OB_STRIDE + (r & 7) * 64 + (lane & 3) * 16 + ((lane >> 2) & 1) * 8, h2_rank));
    const uint32_t h2_bar = pin(mapa(obar, h2_rank));
    const uint32_t h2_src = pin(sb + OFF_HOP + (w & 3) * 512 + (lane & 7) * 16);
    const uint32_t h2_wait = pin(hbar + 8 * (w & 3));
    const uint32_t bars = pin(obar);
    const uint32_t wo_src = pin(sb + (((lane >> 3) & 1) * 16 + (lane >> 4) * 8 + (lane & 7)) * 128 + ((w ^ (lane & 7)) << 4));
    const uint32_t ob_src = pin(sb + OFF_OB + (g & 3) * OB_STRIDE + (g >> 2) * 64 + t * 16);
    unsigned long long* acc_p = pin_ptr(acc + (c * 16 + (j >> 4)) * 32 + (j & 15));
    __nv_bfloat16* out_p = pin_ptr(out + (g & 3) * 448 + c * 64 + w * 8 + 2 * t + (g >> 2));
    const uint32_t k_one = pin(zero + 1u);
    const bool t_hi = pin(t >> 1) != 0, g_hi = pin(g >> 2) != 0, proj_on = pin(proj ? 1u : 0u) != 0;

    float acc0[4] = {0.f, 0.f, 0.f, 0.f}, acc1[4] = {0.f, 0.f, 0.f, 0.f};
    float wgt;
    {
        const uint32_t va0 = pin(sb + (w >> 1) * 2048 + ((lane >> 4) * 8 + (lane & 7)) * 128 + ((((w & 1) * 4 + ((lane >> 3) & 1)) ^ (lane & 7)) << 4));
        const uint32_t va1 = pin(va0 ^ 32);
        const uint32_t pa = pin(sb + OFF_PS + ((g >> 1) & 1) * 32 + t * 8);
        const uint32_t vb = bars - (obar - vfull);
#pragma unroll 1
        for (int k = 0; k < 8; k += 2) {
            const uint32_t so = (k < 4 ? k + 8 : k - 4) * 8192;
            const uint2 p0 = lds64(pa + k * 64), p1 = lds64(pa + k * 64 + 64);
            mbar_wait(vb + 8 * k);
            const uint4 f0 = ldsm4t(va0 + so), f1 = ldsm4t(va1 + so);
            mma16816(acc0, f0, p0.x, p0.y);
            mma16816(acc1, f1, p0.x, p0.y);
            mbar_wait(vb + 8 * k + 8);
            const uint4 f2 = ldsm4t(va0 + so + 8192), f3 = ldsm4t(va1 + so + 8192);
            mma16816(acc0, f2, p1.x, p1.y);
            mma16816(acc1, f3, p1.x, p1.y);
            slot_release(empty + 8 * (10 + (k >> 1)), fu(acc0[0]) ^ fu(acc1[0]), zero, lane);
        }
        uint2 pw[8];
#pragma unroll
        for (int k = 8; k < 16; k++) pw[k - 8] = lds64(pa + k * 64);
        {
            mbar_wait(stbar);
            const uint32_t sa = sb + OFF_WST + 128 + (t & 1) * 8;
            const float2 z0 = lds64f(sa), z1 = lds64f(sa + 16), z2 = lds64f(sa + 32), z3 = lds64f(sa + 48);
            const float mx = fmaxf(fmaxf(z0.x, z1.x), fmaxf(z2.x, z3.x));
            const float W = (ex2(z0.x - mx) * z0.y + ex2(z1.x - mx) * z1.y) + (ex2(z2.x - mx) * z2.y + ex2(z3.x - mx) * z3.y);
            wgt = __uint_as_float(pin(fu(__fdividef(ex2(Mown - mx), W))));
        }
        uint4 f0, f1;
#pragma unroll
        for (int k = 8; k < 16; k++) {
            mbar_wait_fast(vb + 8 * k);
            if (k == 15) GT_AT(1);
            const uint4 n0 = ldsm4t(va0 + (k - 4) * 8192), n1 = ldsm4t(va1 + (k - 4) * 8192);
            if (k > 8) {
                mma16816(acc0, f0, pw[k - 9].x, pw[k - 9].y);
                mma16816(acc1, f1, pw[k - 9].x, pw[k - 9].y);
            }
            f0 = n0; f1 = n1;
        }
        mma16816(acc0, f0, pw[7].x, pw[7].y);
        mma16816(acc1, f1, pw[7].x, pw[7].y);
    }
    st_async64(h1_dst, fu((t_hi ? acc1[0] : acc0[0]) * wgt), fu((t_hi ? acc1[2] : acc0[2]) * wgt), h1_bar);
    {
        mbar_wait_fast(h2_wait);
        const float4 v0 = lds128f(h2_src), v1 = lds128f(h2_src + 128), v2 = lds128f(h2_src + 256), v3 = lds128f(h2_src + 384);
        st_async64(h2_dst, pack_bf16((v0.x + v1.x) + (v2.x + v3.x), (v0.z + v1.z) + (v2.z + v3.z)),
                   pack_bf16((v0.y + v1.y) + (v2.y + v3.y), (v0.w + v1.w) + (v2.w + v3.w)), h2_bar);
    }
    if (!proj_on) {
        mbar_wait_fast(bars);
        GT_END();
        return;
    }
    float sum;
    {
        const uint32_t ob = bars - (obar - ofull);
        float x0[4] = {0.f, 0.f, 0.f, 0.f}, x1[4] = {0.f, 0.f, 0.f, 0.f}, y0[4] = {0.f, 0.f, 0.f, 0.f}, y1[4] = {0.f, 0.f, 0.f, 0.f};
        uint4 bp[4], bq[4], oa[4];
#pragma unroll
        for (int n = 0; n < 4; n++) {
            if (n == PRE) {
                mbar_wait_fast(bars);
                GT_AT(5);
#pragma unroll
                for (int i = 0; i < 4; i++) oa[i] = lds128(ob_src + i * 128);
#pragma unroll
                for (int i = 0; i < PRE; i++) {
                    mma16816(x0, oa[i], bp[i].x, bp[i].y);
                    mma16816(y0, oa[i], bp[i].z, bp[i].w);
                    mma16816(x1, oa[i], bq[i].x, bq[i].y);
                    mma16816(y1, oa[i], bq[i].z, bq[i].w);
                }
            }
            mbar_wait_fast(ob + 8 * n);
            if (n == 3) GT_AT(4);
            bp[n] = ldsm4t(wo_src + n * 8192);
            bq[n] = ldsm4t(wo_src + n * 8192 + 4096);
            if (n > PRE) {
                mma16816(x0, oa[n - 1], bp[n - 1].x, bp[n - 1].y);
                mma16816(y0, oa[n - 1], bp[n - 1].z, bp[n - 1].w);
                mma16816(x1, oa[n - 1], bq[n - 1].x, bq[n - 1].y);
                mma16816(y1, oa[n - 1], bq[n - 1].z, bq[n - 1].w);
            }
        }
        mma16816(x0, oa[3], bp[3].x, bp[3].y);
        mma16816(y0, oa[3], bp[3].z, bp[3].w);
        mma16816(x1, oa[3], bq[3].x, bq[3].y);
        mma16816(y1, oa[3], bq[3].z, bq[3].w);
        float keep = x0[0] + y0[2], send = x0[1] + y0[3];
        if (g_hi) { send = x1[0] + y1[2]; keep = x1[1] + y1[3]; }
        sum = keep + __shfl_xor_sync(0xffffffffu, send, 16);
    }
    const uint32_t bits = fu(sum);
    const uint32_t sh = 129u - ((bits >> 23) & 0xFFu);
    const uint32_t smant = (((bits << 3) & 0x3FFFFF8u) | 0x4000000u) ^ (uint32_t)((int)bits >> 31);
    long long fx;
    asm("shr.s64 %0, %1, %2;" : "=l"(fx) : "l"((long long)((unsigned long long)smant << 32)), "r"(sh));
    const unsigned long long inc = ((unsigned long long)fx & 0xFFFFFFFF00000000ull) | (((uint32_t)fx & ~0x3FFu) | k_one);
    const bool fast = __any_sync(0xffffffffu, fabsf(sum) >= 0x1p-30f) && fabsf(sum) < 8.0f;
    GT_AT(7);
    unsigned long long tot = 0ull;
    asm volatile("{\n.reg .pred p;\nsetp.ne.u32 p, %3, 0;\n@p atom.relaxed.gpu.global.add.u64 %0, [%1], %2;\n}"
                 : "+l"(tot) : "l"(acc_p), "l"(inc), "r"((uint32_t)fast) : "memory");
    if (!fast) { accumulate_slow(sum, acc_p, out_p); return; }
    tot += inc;
    const uint32_t cnt = (uint32_t)tot & 0x3FFu;
    asm volatile("{\n.reg .pred p;\nsetp.eq.u32 p, %3, 16;\n@p st.global.u16 [%0], %1;\n@p st.global.u64 [%2], 0;\n}"
                 ::"l"(out_p), "h"(__bfloat16_as_ushort(__float2bfloat16(acc_value(tot)))), "l"(acc_p), "r"(cnt) : "memory");
    if (cnt > 16u) finish_with_side(tot, acc_p, out_p);
    GT_END();
}

typedef CUresult (*EncodeFn)(CUtensorMap*, CUtensorMapDataType, cuuint32_t, void*, const cuuint64_t*, const cuuint64_t*,
                             const cuuint32_t*, const cuuint32_t*, CUtensorMapInterleave, CUtensorMapSwizzle,
                             CUtensorMapL2promotion, CUtensorMapFloatOOBfill);

}

extern "C" void kernel_launch(void* const* d_in, const int* in_sizes, int n_in, void* d_out, int out_size) {
    (void)in_sizes; (void)n_in; (void)out_size;
    static EncodeFn encode = nullptr;
    static void* acc = nullptr;
    if (!encode) {
        cudaDriverEntryPointQueryResult qr;
        cudaGetDriverEntryPoint("cuTensorMapEncodeTiled", (void**)&encode, cudaEnableDefault, &qr);
        cudaGetSymbolAddress(&acc, g_acc);
        cudaFuncSetAttribute(decode_kernel, cudaFuncAttributeMaxDynamicSharedMemorySize, SMEM_BYTES);
        cudaFuncSetAttribute(decode_kernel, cudaFuncAttributeNonPortableClusterSizeAllowed, 1);
    }
    const cuuint32_t estr[3] = {1, 1, 1};
    CUtensorMap wq_map, wo_map, v_map;
    {
        const cuuint64_t dim[2] = {4096, 448}, str[1] = {8192};
        const cuuint32_t box[2] = {64, 224};
        encode(&wq_map, CU_TENSOR_MAP_DATA_TYPE_BFLOAT16, 2, d_in[3], dim, str, box, estr, CU_TENSOR_MAP_INTERLEAVE_NONE,
               CU_TENSOR_MAP_SWIZZLE_128B, CU_TENSOR_MAP_L2_PROMOTION_NONE, CU_TENSOR_MAP_FLOAT_OOB_FILL_NONE);
    }
    {
        const cuuint64_t dim[2] = {448, 4096}, str[1] = {896};
        const cuuint32_t box[2] = {64, 64};
        encode(&wo_map, CU_TENSOR_MAP_DATA_TYPE_BFLOAT16, 2, d_in[4], dim, str, box, estr, CU_TENSOR_MAP_INTERLEAVE_NONE,
               CU_TENSOR_MAP_SWIZZLE_128B, CU_TENSOR_MAP_L2_PROMOTION_NONE, CU_TENSOR_MAP_FLOAT_OOB_FILL_NONE);
    }
    {
        const cuuint64_t dim[3] = {64, 4ull * 8 * SK, 4}, str[2] = {512, 128};
        const cuuint32_t box[3] = {64, 16, 4};
        encode(&v_map, CU_TENSOR_MAP_DATA_TYPE_BFLOAT16, 3, d_in[2], dim, str, box, estr, CU_TENSOR_MAP_INTERLEAVE_NONE,
               CU_TENSOR_MAP_SWIZZLE_128B, CU_TENSOR_MAP_L2_PROMOTION_NONE, CU_TENSOR_MAP_FLOAT_OOB_FILL_NONE);
    }
    cudaLaunchConfig_t cfg = {};
    cfg.gridDim = dim3(128);
    cfg.blockDim = dim3(NTHREADS);
    cfg.dynamicSmemBytes = SMEM_BYTES;
    cfg.stream = cudaStreamPerThread;
    cudaLaunchAttribute attr[2];
    attr[0].id = cudaLaunchAttributeClusterDimension;
    attr[0].val.clusterDim.x = 16; attr[0].val.clusterDim.y = 1; attr[0].val.clusterDim.z = 1;
    attr[1].id = cudaLaunchAttributeClusterSchedulingPolicyPreference;
    attr[1].val.clusterSchedulingPolicyPreference = cudaClusterSchedulingPolicyLoadBalancing;
    cfg.attrs = attr;
    cfg.numAttrs = 2;
    cudaLaunchKernelEx(&cfg, decode_kernel, (const __nv_bfloat16*)d_in[0], (const __nv_bfloat16*)d_in[1],
                       (const __nv_bfloat16*)d_in[3], (__nv_bfloat16*)d_out, (unsigned long long*)acc, 0u,
                       wq_map, wo_map, v_map);
}
```

```cpp
#include <cuda_runtime.h>
#include <cuda_bf16.h>
#include <cuda.h>
#include <stdint.h>

namespace {

constexpr int SK = 4096, WIN0 = 3072;
constexpr int SLOT = 16384;
constexpr int OFF_BAR  = 6 * SLOT;
constexpr int OFF_QBUF = OFF_BAR + 416;
constexpr int OFF_QS   = OFF_QBUF + 4096;
constexpr int OFF_WST  = OFF_QS + 1024;
constexpr int OB_STRIDE = 576;
constexpr int OFF_OB   = OFF_WST + 192;
constexpr int OFF_HOP  = OFF_OB + 4 * OB_STRIDE;
constexpr int OFF_QRED = OFF_HOP + 2048;
constexpr int OFF_PS   = OFF_QRED;
constexpr int SMEM_BYTES = OFF_QRED + 7 * 1024;
static_assert(SMEM_BYTES <= 115712, "two CTAs must fit on one SM");
constexpr int NTHREADS = 288;
constexpr int SPIN_LIMIT = 1 << 20;

#define TK0 500
#define TDV 331
#define TGAP 0
#define TDO 250
#define T7 1600
#define WLK 2
#define WLV 4
#define PRE 3
#define NOST 0
#define TDK (2 * TDV)
#define WLO 1

constexpr int ACC_WORDS = 1792 * 2;
__device__ __align__(1024) unsigned long long g_acc[ACC_WORDS];
__device__ float g_side[ACC_WORDS];

#define GT_AT(n)
#define GT_END()

__device__ __forceinline__ void mbar_init(uint32_t bar, uint32_t cnt) {
    asm volatile("mbarrier.init.shared::cta.b64 [%0], %1;" ::"r"(bar), "r"(cnt) : "memory");
}
__device__ __forceinline__ void mbar_expect_tx(uint32_t bar, uint32_t bytes) {
    asm volatile("mbarrier.arrive.expect_tx.shared::cta.b64 _, [%0], %1;" ::"r"(bar), "r"(bytes) : "memory");
}
__device__ __forceinline__ void slot_release(uint32_t bar, uint32_t dep, uint32_t zero, int lane) {
    if (lane == 0) asm volatile("mbarrier.arrive.shared::cta.b64 _, [%0];" ::"r"(bar + (dep & zero)) : "memory");
}
__device__ __forceinline__ void mbar_wait_n(uint32_t bar, uint32_t& n) {
    asm volatile("{\n.reg .pred p, q;\n"
                 "WAIT_LOOP:\n"
                 "mbarrier.try_wait.parity.shared::cta.b64 p, [%1], 0;\n"
                 "add.u32 %0, %0, 1;\n"
                 "setp.lt.and.u32 q, %0, %2, !p;\n"
                 "@q bra.uni WAIT_LOOP;\n}"
                 : "+r"(n) : "r"(bar), "n"(SPIN_LIMIT) : "memory");
}
#define mbar_wait(bar) mbar_wait_n(bar, spins)
__device__ __forceinline__ void mbar_wait_fast(uint32_t bar) {
    asm volatile("{\n.reg .pred p;\nWAIT_LOOP:\nmbarrier.try_wait.parity.shared::cta.b64 p, [%0], 0;\n@!p bra.uni WAIT_LOOP;\n}"
                 ::"r"(bar) : "memory");
}
__device__ __forceinline__ uint32_t now_ns() {
    uint32_t t;
    asm volatile("mov.u32 %0, %%globaltimer_lo;" : "=r"(t)::"memory");
    return t;
}
__device__ __forceinline__ void pace(uint32_t due, uint32_t bar) {
    while ((int)(now_ns() - due) < 0) {
        uint32_t ok;
        asm volatile("{\n.reg .pred p;\nmbarrier.test_wait.parity.shared::cta.b64 p, [%1], 0;\nselp.u32 %0, 1, 0, p;\n}"
                     : "=r"(ok) : "r"(bar) : "memory");
        if (ok) break;
    }
}
__device__ __forceinline__ void bulk_g2s(uint32_t dst, const void* src, uint32_t bytes, uint32_t bar) {
    asm volatile("cp.async.bulk.shared::cluster.global.mbarrier::complete_tx::bytes [%0], [%1], %2, [%3];"
                 ::"r"(dst), "l"(src), "r"(bytes), "r"(bar) : "memory");
}
__device__ __forceinline__ void bulk_g2s_mc(uint32_t dst, const void* src, uint32_t bytes, uint32_t bar, uint16_t mask) {
    asm volatile("cp.async.bulk.shared::cluster.global.mbarrier::complete_tx::bytes.multicast::cluster [%0], [%1], %2, [%3], %4;"
                 ::"r"(dst), "l"(src), "r"(bytes), "r"(bar), "h"(mask) : "memory");
}
__device__ __forceinline__ void tma2d(uint32_t dst, const CUtensorMap* tm, int c0, int c1, uint32_t bar) {
    asm volatile("cp.async.bulk.tensor.2d.shared::cluster.global.mbarrier::complete_tx::bytes [%0], [%1, {%3, %4}], [%2];"
                 ::"r"(dst), "l"(tm), "r"(bar), "r"(c0), "r"(c1) : "memory");
}
__device__ __forceinline__ void tma3d(uint32_t dst, const CUtensorMap* tm, int c1, uint32_t bar) {
    asm volatile("cp.async.bulk.tensor.3d.shared::cluster.global.mbarrier::complete_tx::bytes [%0], [%1, {%3, %4, %3}], [%2];"
                 ::"r"(dst), "l"(tm), "r"(bar), "r"(0), "r"(c1) : "memory");
}
__device__ __forceinline__ uint32_t pin(uint32_t v) {
    uint32_t o;
    asm volatile("shfl.sync.bfly.b32 %0, %1, 0, 0x1f, 0xffffffff;" : "=r"(o) : "r"(v));
    return o;
}
template <typename T> __device__ __forceinline__ T* pin_ptr(T* p) {
    const unsigned long long a = (unsigned long long)p;
    return (T*)(((unsigned long long)pin((uint32_t)(a >> 32)) << 32) | pin((uint32_t)a));
}
__device__ __forceinline__ bool elect_one() {
    uint32_t p;
    asm volatile("{\n.reg .pred P;\nelect.sync _|P, 0xffffffff;\nselp.u32 %0, 1, 0, P;\n}" : "=r"(p));
    return p != 0;
}
__device__ __forceinline__ void bar_compute() { asm volatile("bar.sync 1, 256;" ::: "memory"); }
__device__ __forceinline__ void cluster_arrive() { asm volatile("barrier.cluster.arrive.relaxed.aligned;" ::: "memory"); }
__device__ __forceinline__ void cluster_wait() { asm volatile("barrier.cluster.wait.aligned;" ::: "memory"); }
__device__ __forceinline__ void fence_mbar_init() { asm volatile("fence.mbarrier_init.release.cluster;" ::: "memory"); }
__device__ __forceinline__ uint32_t mapa(uint32_t a, uint32_t rank) {
    uint32_t o;
    asm("mapa.shared::cluster.u32 %0, %1, %2;" : "=r"(o) : "r"(a), "r"(rank));
    return o;
}
__device__ __forceinline__ void st_async128(uint32_t a, uint32_t x, uint32_t y, uint32_t z, uint32_t w, uint32_t bar) {
    asm volatile("st.async.shared::cluster.mbarrier::complete_tx::bytes.v4.b32 [%0], {%1,%2,%3,%4}, [%5];"
                 ::"r"(a), "r"(x), "r"(y), "r"(z), "r"(w), "r"(bar) : "memory");
}
__device__ __forceinline__ void st_async64(uint32_t a, uint32_t x, uint32_t y, uint32_t bar) {
    asm volatile("st.async.shared::cluster.mbarrier::complete_tx::bytes.v2.b32 [%0], {%1,%2}, [%3];"
                 ::"r"(a), "r"(x), "r"(y), "r"(bar) : "memory");
}
__device__ __forceinline__ void mma16816(float (&c)[4], const uint4& a, uint32_t b0, uint32_t b1) {
    asm volatile("mma.sync.aligned.m16n8k16.row.col.f32.bf16.bf16.f32 {%0,%1,%2,%3}, {%4,%5,%6,%7}, {%8,%9}, {%0,%1,%2,%3};"
                 : "+f"(c[0]), "+f"(c[1]), "+f"(c[2]), "+f"(c[3])
                 : "r"(a.x), "r"(a.y), "r"(a.z), "r"(a.w), "r"(b0), "r"(b1));
}
__device__ __forceinline__ uint4 lds128(uint32_t a) {
    uint4 v;
    asm volatile("ld.shared.v4.u32 {%0,%1,%2,%3}, [%4];" : "=r"(v.x), "=r"(v.y), "=r"(v.z), "=r"(v.w) : "r"(a) : "memory");
    return v;
}
__device__ __forceinline__ float4 lds128f(uint32_t a) {
    float4 v;
    asm volatile("ld.shared.v4.f32 {%0,%1,%2,%3}, [%4];" : "=f"(v.x), "=f"(v.y), "=f"(v.z), "=f"(v.w) : "r"(a) : "memory");
    return v;
}
__device__ __forceinline__ float2 lds64f(uint32_t a) {
    float2 v;
    asm volatile("ld.shared.v2.f32 {%0,%1}, [%2];" : "=f"(v.x), "=f"(v.y) : "r"(a) : "memory");
    return v;
}
__device__ __forceinline__ uint2 lds64(uint32_t a) {
    uint2 v;
    asm volatile("ld.shared.v2.u32 {%0,%1}, [%2];" : "=r"(v.x), "=r"(v.y) : "r"(a) : "memory");
    return v;
}
__device__ __forceinline__ uint32_t lds32(uint32_t a) {
    uint32_t v;
    asm volatile("ld.shared.u32 %0, [%1];" : "=r"(v) : "r"(a) : "memory");
    return v;
}
__device__ __forceinline__ float lds32f(uint32_t a) { return __uint_as_float(lds32(a)); }
__device__ __forceinline__ void sts128f(uint32_t a, float x, float y, float z, float w) {
    asm volatile("st.shared.v4.f32 [%0], {%1,%2,%3,%4};" ::"r"(a), "f"(x), "f"(y), "f"(z), "f"(w) : "memory");
}
__device__ __forceinline__ void sts32(uint32_t a, uint32_t v) {
    asm volatile("st.shared.u32 [%0], %1;" ::"r"(a), "r"(v) : "memory");
}
__device__ __forceinline__ void sts16(uint32_t a, unsigned short v) {
    asm volatile("st.shared.u16 [%0], %1;" ::"r"(a), "h"(v) : "memory");
}
__device__ __forceinline__ uint4 ldsm4t(uint32_t a) {
    uint4 v;
    asm volatile("ldmatrix.sync.aligned.m8n8.x4.trans.shared.b16 {%0,%1,%2,%3}, [%4];"
                 : "=r"(v.x), "=r"(v.y), "=r"(v.z), "=r"(v.w) : "r"(a) : "memory");
    return v;
}
__device__ __forceinline__ uint32_t pack_bf16(float lo, float hi) {
    uint32_t r;
    asm("cvt.rn.bf16x2.f32 %0, %1, %2;" : "=r"(r) : "f"(hi), "f"(lo));
    return r;
}
__device__ __forceinline__ float round_bf16(float v) { return __uint_as_float(pack_bf16(0.f, v) & 0xFFFF0000u); }
__device__ __forceinline__ float ex2(float x) {
    float y;
    asm("ex2.approx.ftz.f32 %0, %1;" : "=f"(y) : "f"(x));
    return y;
}
__device__ __forceinline__ uint32_t fu(float v) { return __float_as_uint(v); }

__device__ __forceinline__ float acc_value(unsigned long long tot) {
    return fmaf((float)(int)(uint32_t)(tot >> 32), 0x1p-24f, (float)((uint32_t)tot >> 10) * 0x1p-46f);
}
__device__ __noinline__ void finish_with_side(unsigned long long tot, unsigned long long* acc_p, __nv_bfloat16* out_p) {
    if ((tot & 31ull) != 16ull) return;
    __threadfence();
    const float side = atomicExch(&g_side[acc_p - g_acc], 0.0f);
    *out_p = __float2bfloat16(acc_value(tot) + side);
    *acc_p = 0ull;
}
__device__ __noinline__ void accumulate_slow(float sum, unsigned long long* acc_p, __nv_bfloat16* out_p) {
    atomicAdd(&g_side[acc_p - g_acc], sum);
    __threadfence();
    finish_with_side(atomicAdd(acc_p, 33ull) + 33ull, acc_p, out_p);
}

__global__ void __launch_bounds__(NTHREADS, 2)
decode_kernel(const __nv_bfloat16* __restrict__ x, const __nv_bfloat16* __restrict__ kc,
              const __nv_bfloat16* __restrict__ wq, __nv_bfloat16* __restrict__ out,
              unsigned long long* __restrict__ acc, const uint32_t zero,
              const __grid_constant__ CUtensorMap wq_map, const __grid_constant__ CUtensorMap wo_map,
              const __grid_constant__ CUtensorMap v_map) {
    asm volatile("prefetch.global.L2 [%0];" ::"l"((const char*)wq + (blockIdx.x * 224 + min(threadIdx.x, 223u)) * 128));

    extern __shared__ __align__(1024) unsigned char smem[];
    const uint32_t sb = (uint32_t)__cvta_generic_to_shared(smem);
    const int warp = threadIdx.x >> 5, lane = threadIdx.x & 31;
    const int cta = blockIdx.x;
    const int gk = cta >> 4, r = cta & 15, b = r >> 2, s = r & 3;
    const bool proj = r < 14;
    const int c = r - 7 * (r >= 7);
    const uint32_t qfull = sb + OFF_BAR, kfull = qfull + 8, vfull = kfull + 64, ofull = vfull + 128, empty = ofull + 32;
    const uint32_t qbar = empty + 14 * 8, stbar = qbar + 8, obar = qbar + 16, hbar = qbar + 24;
    uint32_t spins = 0;

    if (warp == 0) {
        const bool leader = elect_one();
        if (leader) {
            mbar_init(qfull, 1);
            mbar_expect_tx(qfull, 28672 + 3584);
            tma2d(sb, &wq_map, (cta >> 1) * 64, (cta & 1) * 224, qfull);
            fence_mbar_init();
        }
        uint32_t due = now_ns() + TK0 - (gk == 7 ? T7 : 0);
        __syncwarp();
        cluster_arrive();
        cluster_wait();
        if (leader) {
            if (proj) bulk_g2s_mc(sb + OFF_OB + r * 256, (const char*)x + r * 256, 256, qfull, (uint16_t)0xFFFF);
            int row = (b * 8 + gk) * SK + WIN0 + s * 256;
            const char* kp = (const char*)kc + (size_t)row * 512;
            uint32_t bar = kfull, dst = sb + 2 * SLOT;
#pragma unroll 1
            for (int i = 0; i < 8; i++) {
                mbar_expect_tx(bar, 16384);
                if (i >= 4) mbar_wait(empty + 8 * (i - 4));
                pace(due, i < WLK ? qfull : bar - 8 * WLK);
                bulk_g2s(dst, kp, 16384, bar);
                if (i == 1) {
                    asm volatile("prefetch.tensormap [%0];" ::"l"(&v_map) : "memory");
                    asm volatile("prefetch.tensormap [%0];" ::"l"(&wo_map) : "memory");
                }
                due += TDK;
                kp += 16384;
                bar += 8;
                dst = (i == 3) ? sb : dst + SLOT;
            }
#pragma unroll 1
            for (int k = 0; k < 16; k++) {
                mbar_expect_tx(bar, 8192);
                mbar_wait(empty + 8 * (4 + (k >> 1)));
                const int d = k - WLV;
                pace(due, vfull + 8 * (d < 0 ? (d >> 1) : d));
                tma3d(dst, &v_map, row, bar);
                due += TDV;
                row += 16;
                bar += 8;
                dst = (k == 3) ? sb : dst + 8192;
            }
            if (proj) {
                due += TGAP;
                mbar_wait(empty + 8 * 12);
                mbar_wait(empty + 8 * 13);
#pragma unroll 1
                for (int n = 0; n < 4; n++) {
                    mbar_expect_tx(bar, 8192);
                    pace(due, bar - 8 * WLO);
                    tma2d(sb + n * 8192, &wo_map, c * 64, (2 * gk + (r >= 7)) * 256 + n * 64, bar);
                    due += TDO;
                    bar += 8;
                }
            }
        }
        return;
    }

    const int w = warp - 1, j = threadIdx.x - 32;
    const int g = lane >> 2, t = lane & 3;

    if (w < 7) {
        cluster_arrive();
        cluster_wait();
        const uint32_t qa = sb + (w * 32 + (lane >> 4) * 8 + (lane & 7)) * 128;
        const uint32_t xa = sb + OFF_OB + (g & 3) * 896 + (cta & 1) * 448 + w * 64 + t * 4;
        mbar_wait(qfull);
        const uint32_t x0 = lds32(xa), x1 = lds32(xa + 16), x2 = lds32(xa + 32), x3 = lds32(xa + 48);
        float cq[4][4];
#pragma unroll
        for (int m = 0; m < 4; m++) {
            const uint32_t a = qa + (((2 * m + ((lane >> 3) & 1)) ^ (lane & 7)) << 4);
            const uint4 f0 = ldsm4t(a), f1 = ldsm4t(a + 2048);
            cq[m][0] = cq[m][1] = cq[m][2] = cq[m][3] = 0.f;
            mma16816(cq[m], f0, x0, x1);
            mma16816(cq[m], f1, x2, x3);
        }
        slot_release(empty + 8 * (w >> 2), fu(cq[0][0]) ^ fu(cq[1][0]) ^ fu(cq[2][0]) ^ fu(cq[3][0]), zero, lane);
        const int hf = t >> 1;
        const uint32_t qr = sb + OFF_QRED + w * 1024 + (t & 1) * 512 + hf * 128 + g * 16;
        sts128f(qr, hf ? cq[0][2] : cq[0][0], hf ? cq[1][2] : cq[1][0], hf ? cq[2][2] : cq[2][0], hf ? cq[3][2] : cq[3][0]);
        sts128f(qr + 256, hf ? cq[0][3] : cq[0][1], hf ? cq[1][3] : cq[1][1], hf ? cq[2][3] : cq[2][1], hf ? cq[3][3] : cq[3][1]);
    } else {
        if (lane == 0) {
#pragma unroll
            for (int i = 0; i < 28; i++) mbar_init(kfull + 8 * i, 1);
#pragma unroll
            for (int i = 0; i < 14; i++) mbar_init(empty + 8 * i, i == 1 ? 3 : (i < 10 ? 4 : 8));
#pragma unroll
            for (int i = 0; i < 7; i++) mbar_init(qbar + 8 * i, 1);
            mbar_expect_tx(qbar, 4096);
            mbar_expect_tx(stbar, 64);
            mbar_expect_tx(obar, 2048);
#pragma unroll
            for (int i = 0; i < 4; i++) mbar_expect_tx(hbar + 8 * i, 512);
            fence_mbar_init();
        }
        __syncwarp();
        cluster_arrive();
        cluster_wait();
    }
    bar_compute();
    {
        const int pk = j >> 2;
        const uint32_t ra = sb + OFF_QRED + pk * 16;
        float4 a = lds128f(ra);
#pragma unroll
        for (int ww = 1; ww < 7; ww++) {
            const float4 v = lds128f(ra + ww * 1024);
            a.x += v.x; a.y += v.y; a.z += v.z; a.w += v.w;
        }
        const uint32_t dst = (pk >> 4) * 4 + (j & 3);
        st_async128(mapa(sb + OFF_QBUF + (r & 1) * 2048 + (r >> 1) * 256 + (pk & 15) * 16, dst),
                    fu(a.x), fu(a.y), fu(a.z), fu(a.w), mapa(qbar, dst));
        mbar_wait(qbar);
        const uint32_t qb = sb + OFF_QBUF + (j >> 5) * 256 + (j & 7) * 32 + ((j >> 3) & 3) * 4;
        const float q0 = lds32f(qb) + lds32f(qb + 2048), q1 = lds32f(qb + 16) + lds32f(qb + 2064);
        sts32(sb + OFF_QS + ((j >> 5) & 3) * 256 + (j & 1) * 128 + (j >> 7) * 64 + ((j >> 2) & 3) * 16 + ((j >> 4) & 1) * 8 + ((j >> 1) & 1) * 4,
              pack_bf16(q0, q1));
    }
    bar_compute();

    float s0 = 0.f, s1 = 0.f;
    {
        uint2 qf[8];
        const uint32_t qa = sb + OFF_QS + (g >> 2) * 128 + (g & 1) * 64 + t * 16;
        const uint32_t qx = ((g >> 1) & 1) * 8;
#pragma unroll
        for (int i = 0; i < 8; i++) qf[i] = lds64(qa + (i >> 1) * 256 + (((i & 1) * 8) ^ qx));
        const uint32_t kx = (g & 1) * 64;
        const uint32_t krow = sb + ((w & 3) * 8 + g) * 512 + t * 16;
        const int src = (lane & 28) + (g & 1);
#pragma unroll 1
        for (int k = 0; k < 4; k++) {
            const int ch = 2 * k + (w >> 2);
            const uint32_t ka = krow + (ch >= 4 ? ch - 4 : ch + 2) * SLOT;
            mbar_wait(kfull + 8 * ch);
            float a0[4] = {0.f, 0.f, 0.f, 0.f}, a1[4] = {0.f, 0.f, 0.f, 0.f};
#pragma unroll
            for (int i = 0; i < 8; i += 2) {
                const uint4 r0 = lds128(ka + ((i * 64) ^ kx)), r1 = lds128(ka + (((i + 1) * 64) ^ kx));
                mma16816(a0, r0, qf[i].x, qf[i].y);
                mma16816(a1, r1, qf[i + 1].x, qf[i + 1].y);
            }
            const float e0 = __shfl_sync(0xffffffffu, a0[0] + a1[0], src) + __shfl_sync(0xffffffffu, a0[2] + a1[2], src + 2);
            const float e1 = __shfl_sync(0xffffffffu, a0[1] + a1[1], src) + __shfl_sync(0xffffffffu, a0[3] + a1[3], src + 2);
            slot_release(empty + 8 * (2 + ch), fu(e0), zero, lane);
            if (t == k) { s0 = e0; s1 = e1; }
        }
    }
    float Mown;
    {
        const float kscale = 0.0625f * 1.4426950408889634f;
        s0 = round_bf16(s0) * kscale;
        s1 = round_bf16(s1) * kscale;
        float m0 = s0, m1 = s1;
#pragma unroll
        for (int o = 16; o > 0; o >>= 1) {
            m0 = fmaxf(m0, __shfl_xor_sync(0xffffffffu, m0, o));
            m1 = fmaxf(m1, __shfl_xor_sync(0xffffffffu, m1, o));
        }
        if (lane < 2) sts32(sb + OFF_WST + (w * 2 + lane) * 4, fu(lane ? m1 : m0));
        bar_compute();
        const float4 u0 = lds128f(sb + OFF_WST), u1 = lds128f(sb + OFF_WST + 16), u2 = lds128f(sb + OFF_WST + 32), u3 = lds128f(sb + OFF_WST + 48);
        const float M0 = fmaxf(fmaxf(fmaxf(u0.x, u0.z), fmaxf(u1.x, u1.z)), fmaxf(fmaxf(u2.x, u2.z), fmaxf(u3.x, u3.z)));
        const float M1 = fmaxf(fmaxf(fmaxf(u0.y, u0.w), fmaxf(u1.y, u1.w)), fmaxf(fmaxf(u2.y, u2.w), fmaxf(u3.y, u3.w)));
        Mown = (t & 1) ? M1 : M0;
        const uint32_t p = pack_bf16(ex2(s0 - M0), ex2(s1 - M1));
        const uint32_t pa = sb + OFF_PS + (4 * t + (w >> 1)) * 64 + (g >> 1) * 8 + (w & 1) * 4 + (g & 1) * 2;
        sts16(pa, (unsigned short)(p & 0xFFFFu));
        sts16(pa + 32, (unsigned short)(p >> 16));
        float l0 = __uint_as_float(p << 16), l1 = __uint_as_float(p & 0xFFFF0000u);
#pragma unroll
        for (int o = 16; o > 0; o >>= 1) {
            l0 += __shfl_xor_sync(0xffffffffu, l0, o);
            l1 += __shfl_xor_sync(0xffffffffu, l1, o);
        }
        if (lane < 2) sts32(sb + OFF_WST + 64 + (w * 2 + lane) * 4, fu(lane ? l1 : l0));
        bar_compute();
        if (j < 4) {
            const float4 v0 = lds128f(sb + OFF_WST + 64), v1 = lds128f(sb + OFF_WST + 80), v2 = lds128f(sb + OFF_WST + 96), v3 = lds128f(sb + OFF_WST + 112);
            const float L0 = ((v0.x + v0.z) + (v1.x + v1.z)) + ((v2.x + v2.z) + (v3.x + v3.z));
            const float L1 = ((v0.y + v0.w) + (v1.y + v1.w)) + ((v2.y + v2.w) + (v3.y + v3.w));
            st_async128(mapa(sb + OFF_WST + 128 + s * 16, b * 4 + j), fu(M0), fu(L0), fu(M1), fu(L1), mapa(stbar, b * 4 + j));
        }
    }

    const uint32_t h1_dst = pin(mapa(sb + OFF_HOP + r * 128 + (t >> 1) * 64 + g * 8, (t & 1) * 8 + w));
    const uint32_t h1_bar = pin(mapa(hbar + 8 * b, (t & 1) * 8 + w));
    const uint32_t h2_grp = (w >> 2) * 4 + (lane >> 3);
    const uint32_t h2_rank = h2_grp < 7 ? (r >> 3) * 7 + h2_grp : 14 + (r >> 3);
    const uint32_t h2_dst = pin(mapa(sb + OFF_OB + (w & 3) * OB_STRIDE + (r & 7) * 64 + (lane & 3) * 16 + ((lane >> 2) & 1) * 8, h2_rank));
    const uint32_t h2_bar = pin(mapa(obar, h2_rank));
    const uint32_t h2_src = pin(sb + OFF_HOP + (w & 3) * 512 + (lane & 7) * 16);
    const uint32_t h2_wait = pin(hbar + 8 * (w & 3));
    const uint32_t bars = pin(obar);
    const uint32_t wo_src = pin(sb + (((lane >> 3) & 1) * 16 + (lane >> 4) * 8 + (lane & 7)) * 128 + ((w ^ (lane & 7)) << 4));
    const uint32_t ob_src = pin(sb + OFF_OB + (g & 3) * OB_STRIDE + (g >> 2) * 64 + t * 16);
    unsigned long long* acc_p = pin_ptr(acc + (c * 16 + (j >> 4)) * 32 + (j & 15));
    __nv_bfloat16* out_p = pin_ptr(out + (g & 3) * 448 + c * 64 + w * 8 + 2 * t + (g >> 2));
    const uint32_t k_one = pin(zero + 1u);
    const bool t_hi = pin(t >> 1) != 0, g_hi = pin(g >> 2) != 0, proj_on = pin(proj ? 1u : 0u) != 0;

    float acc0[4] = {0.f, 0.f, 0.f, 0.f}, acc1[4] = {0.f, 0.f, 0.f, 0.f};
    float wgt;
    {
        const uint32_t va0 = pin(sb + (w >> 1) * 2048 + ((lane >> 4) * 8 + (lane & 7)) * 128 + ((((w & 1) * 4 + ((lane >> 3) & 1)) ^ (lane & 7)) << 4));
        const uint32_t va1 = pin(va0 ^ 32);
        const uint32_t pa = pin(sb + OFF_PS + ((g >> 1) & 1) * 32 + t * 8);
        const uint32_t vb = bars - (obar - vfull);
#pragma unroll 1
        for (int k = 0; k < 8; k += 2) {
            const uint32_t so = (k < 4 ? k + 8 : k - 4) * 8192;
            const uint2 p0 = lds64(pa + k * 64), p1 = lds64(pa + k * 64 + 64);
            mbar_wait(vb + 8 * k);
            const uint4 f0 = ldsm4t(va0 + so), f1 = ldsm4t(va1 + so);
            mma16816(acc0, f0, p0.x, p0.y);
            mma16816(acc1, f1, p0.x, p0.y);
            mbar_wait(vb + 8 * k + 8);
            const uint4 f2 = ldsm4t(va0 + so + 8192), f3 = ldsm4t(va1 + so + 8192);
            mma16816(acc0, f2, p1.x, p1.y);
            mma16816(acc1, f3, p1.x, p1.y);
            slot_release(empty + 8 * (10 + (k >> 1)), fu(acc0[0]) ^ fu(acc1[0]), zero, lane);
        }
        uint2 pw[8];
#pragma unroll
        for (int k = 8; k < 16; k++) pw[k - 8] = lds64(pa + k * 64);
        {
            mbar_wait(stbar);
            const uint32_t sa = sb + OFF_WST + 128 + (t & 1) * 8;
            const float2 z0 = lds64f(sa), z1 = lds64f(sa + 16), z2 = lds64f(sa + 32), z3 = lds64f(sa + 48);
            const float mx = fmaxf(fmaxf(z0.x, z1.x), fmaxf(z2.x, z3.x));
            const float W = (ex2(z0.x - mx) * z0.y + ex2(z1.x - mx) * z1.y) + (ex2(z2.x - mx) * z2.y + ex2(z3.x - mx) * z3.y);
            wgt = __uint_as_float(pin(fu(__fdividef(ex2(Mown - mx), W))));
        }
        uint4 f0, f1;
#pragma unroll
        for (int k = 8; k < 16; k++) {
            mbar_wait_fast(vb + 8 * k);
            if (k == 15) GT_AT(1);
            const uint4 n0 = ldsm4t(va0 + (k - 4) * 8192), n1 = ldsm4t(va1 + (k - 4) * 8192);
            if (k > 8) {
                mma16816(acc0, f0, pw[k - 9].x, pw[k - 9].y);
                mma16816(acc1, f1, pw[k - 9].x, pw[k - 9].y);
            }
            f0 = n0; f1 = n1;
        }
        mma16816(acc0, f0, pw[7].x, pw[7].y);
        mma16816(acc1, f1, pw[7].x, pw[7].y);
    }
    st_async64(h1_dst, fu((t_hi ? acc1[0] : acc0[0]) * wgt), fu((t_hi ? acc1[2] : acc0[2]) * wgt), h1_bar);
    {
        mbar_wait_fast(h2_wait);
        const float4 v0 = lds128f(h2_src), v1 = lds128f(h2_src + 128), v2 = lds128f(h2_src + 256), v3 = lds128f(h2_src + 384);
        st_async64(h2_dst, pack_bf16((v0.x + v1.x) + (v2.x + v3.x), (v0.z + v1.z) + (v2.z + v3.z)),
                   pack_bf16((v0.y + v1.y) + (v2.y + v3.y), (v0.w + v1.w) + (v2.w + v3.w)), h2_bar);
    }
    if (!proj_on) {
        mbar_wait_fast(bars);
        GT_END();
        return;
    }
    float sum;
    {
        const uint32_t ob = bars - (obar - ofull);
        float x0[4] = {0.f, 0.f, 0.f, 0.f}, x1[4] = {0.f, 0.f, 0.f, 0.f}, y0[4] = {0.f, 0.f, 0.f, 0.f}, y1[4] = {0.f, 0.f, 0.f, 0.f};
        uint4 bp[4], bq[4], oa[4];
#pragma unroll
        for (int n = 0; n < 4; n++) {
            if (n == PRE) {
                mbar_wait_fast(bars);
                GT_AT(5);
#pragma unroll
                for (int i = 0; i < 4; i++) oa[i] = lds128(ob_src + i * 128);
#pragma unroll
                for (int i = 0; i < PRE; i++) {
                    mma16816(x0, oa[i], bp[i].x, bp[i].y);
                    mma16816(y0, oa[i], bp[i].z, bp[i].w);
                    mma16816(x1, oa[i], bq[i].x, bq[i].y);
                    mma16816(y1, oa[i], bq[i].z, bq[i].w);
                }
            }
            mbar_wait_fast(ob + 8 * n);
            if (n == 3) GT_AT(4);
            bp[n] = ldsm4t(wo_src + n * 8192);
            bq[n] = ldsm4t(wo_src + n * 8192 + 4096);
            if (n > PRE) {
                mma16816(x0, oa[n - 1], bp[n - 1].x, bp[n - 1].y);
                mma16816(y0, oa[n - 1], bp[n - 1].z, bp[n - 1].w);
                mma16816(x1, oa[n - 1], bq[n - 1].x, bq[n - 1].y);
                mma16816(y1, oa[n - 1], bq[n - 1].z, bq[n - 1].w);
            }
        }
        mma16816(x0, oa[3], bp[3].x, bp[3].y);
        mma16816(y0, oa[3], bp[3].z, bp[3].w);
        mma16816(x1, oa[3], bq[3].x, bq[3].y);
        mma16816(y1, oa[3], bq[3].z, bq[3].w);
        float keep = x0[0] + y0[2], send = x0[1] + y0[3];
        if (g_hi) { send = x1[0] + y1[2]; keep = x1[1] + y1[3]; }
        sum = keep + __shfl_xor_sync(0xffffffffu, send, 16);
    }
    const uint32_t bits = fu(sum);
    const uint32_t sh = 129u - ((bits >> 23) & 0xFFu);
    const uint32_t smant = (((bits << 3) & 0x3FFFFF8u) | 0x4000000u) ^ (uint32_t)((int)bits >> 31);
    long long fx;
    asm("shr.s64 %0, %1, %2;" : "=l"(fx) : "l"((long long)((unsigned long long)smant << 32)), "r"(sh));
    const unsigned long long inc = ((unsigned long long)fx & 0xFFFFFFFF00000000ull) | (((uint32_t)fx & ~0x3FFu) | k_one);
    const bool fast = __any_sync(0xffffffffu, fabsf(sum) >= 0x1p-30f) && fabsf(sum) < 8.0f;
    GT_AT(7);
    unsigned long long tot = 0ull;
    asm volatile("{\n.reg .pred p;\nsetp.ne.u32 p, %3, 0;\n@p atom.relaxed.gpu.global.add.u64 %0, [%1], %2;\n}"
                 : "+l"(tot) : "l"(acc_p), "l"(inc), "r"((uint32_t)fast) : "memory");
    if (!fast) { accumulate_slow(sum, acc_p, out_p); return; }
    tot += inc;
    const uint32_t cnt = (uint32_t)tot & 0x3FFu;
    asm volatile("{\n.reg .pred p;\nsetp.eq.u32 p, %3, 16;\n@p st.global.u16 [%0], %1;\n@p st.global.u64 [%2], 0;\n}"
                 ::"l"(out_p), "h"(__bfloat16_as_ushort(__float2bfloat16(acc_value(tot)))), "l"(acc_p), "r"(cnt) : "memory");
    if (cnt > 16u) finish_with_side(tot, acc_p, out_p);
    GT_END();
}

typedef CUresult (*EncodeFn)(CUtensorMap*, CUtensorMapDataType, cuuint32_t, void*, const cuuint64_t*, const cuuint64_t*,
                             const cuuint32_t*, const cuuint32_t*, CUtensorMapInterleave, CUtensorMapSwizzle,
                             CUtensorMapL2promotion, CUtensorMapFloatOOBfill);

}

extern "C" void kernel_launch(void* const* d_in, const int* in_sizes, int n_in, void* d_out, int out_size) {
    (void)in_sizes; (void)n_in; (void)out_size;
    static EncodeFn encode = nullptr;
    static void* acc = nullptr;
    if (!encode) {
        cudaDriverEntryPointQueryResult qr;
        cudaGetDriverEntryPoint("cuTensorMapEncodeTiled", (void**)&encode, cudaEnableDefault, &qr);
        cudaGetSymbolAddress(&acc, g_acc);
        cudaFuncSetAttribute(decode_kernel, cudaFuncAttributeMaxDynamicSharedMemorySize, SMEM_BYTES);
        cudaFuncSetAttribute(decode_kernel, cudaFuncAttributeNonPortableClusterSizeAllowed, 1);
    }
    const cuuint32_t estr[3] = {1, 1, 1};
    CUtensorMap wq_map, wo_map, v_map;
    {
        const cuuint64_t dim[2] = {4096, 448}, str[1] = {8192};
        const cuuint32_t box[2] = {64, 224};
        encode(&wq_map, CU_TENSOR_MAP_DATA_TYPE_BFLOAT16, 2, d_in[3], dim, str, box, estr, CU_TENSOR_MAP_INTERLEAVE_NONE,
               CU_TENSOR_MAP_SWIZZLE_128B, CU_TENSOR_MAP_L2_PROMOTION_NONE, CU_TENSOR_MAP_FLOAT_OOB_FILL_NONE);
    }
    {
        const cuuint64_t dim[2] = {448, 4096}, str[1] = {896};
        const cuuint32_t box[2] = {64, 64};
        encode(&wo_map, CU_TENSOR_MAP_DATA_TYPE_BFLOAT16, 2, d_in[4], dim, str, box, estr, CU_TENSOR_MAP_INTERLEAVE_NONE,
               CU_TENSOR_MAP_SWIZZLE_128B, CU_TENSOR_MAP_L2_PROMOTION_NONE, CU_TENSOR_MAP_FLOAT_OOB_FILL_NONE);
    }
    {
        const cuuint64_t dim[3] = {64, 4ull * 8 * SK, 4}, str[2] = {512, 128};
        const cuuint32_t box[3] = {64, 16, 4};
        encode(&v_map, CU_TENSOR_MAP_DATA_TYPE_BFLOAT16, 3, d_in[2], dim, str, box, estr, CU_TENSOR_MAP_INTERLEAVE_NONE,
               CU_TENSOR_MAP_SWIZZLE_128B, CU_TENSOR_MAP_L2_PROMOTION_NONE, CU_TENSOR_MAP_FLOAT_OOB_FILL_NONE);
    }
    cudaLaunchConfig_t cfg = {};
    cfg.gridDim = dim3(128);
    cfg.blockDim = dim3(NTHREADS);
    cfg.dynamicSmemBytes = SMEM_BYTES;
    cfg.stream = cudaStreamPerThread;
    cudaLaunchAttribute attr[2];
    attr[0].id = cudaLaunchAttributeClusterDimension;
    attr[0].val.clusterDim.x = 16; attr[0].val.clusterDim.y = 1; attr[0].val.clusterDim.z = 1;
    attr[1].id = cudaLaunchAttributeClusterSchedulingPolicyPreference;
    attr[1].val.clusterSchedulingPolicyPreference = cudaClusterSchedulingPolicyLoadBalancing;
    cfg.attrs = attr;
    cfg.numAttrs = 2;
    cudaLaunchKernelEx(&cfg, decode_kernel, (const __nv_bfloat16*)d_in[0], (const __nv_bfloat16*)d_in[1],
                       (const __nv_bfloat16*)d_in[3], (__nv_bfloat16*)d_out, (unsigned long long*)acc, 0u,
                       wq_map, wo_map, v_map);
}
```

```cpp
#include <cuda_runtime.h>
#include <cuda_bf16.h>
#include <cuda.h>
#include <stdint.h>

namespace {

constexpr int SK = 4096, WIN0 = 3072;
constexpr int SLOT = 16384;
constexpr int OFF_BAR  = 6 * SLOT;
constexpr int OFF_QBUF = OFF_BAR + 416;
constexpr int OFF_QS   = OFF_QBUF + 4096;
constexpr int OFF_WST  = OFF_QS + 1024;
constexpr int OB_STRIDE = 576;
constexpr int OFF_OB   = OFF_WST + 192;
constexpr int OFF_HOP  = OFF_OB + 4 * OB_STRIDE;
constexpr int OFF_QRED = OFF_HOP + 2048;
constexpr int OFF_PS   = OFF_QRED;
constexpr int SMEM_BYTES = OFF_QRED + 7 * 1024;
static_assert(SMEM_BYTES <= 115712, "two CTAs must fit on one SM");
constexpr int NTHREADS = 288;
constexpr int SPIN_LIMIT = 1 << 20;

#define TK0 500
#define TDV 331
#define TGAP 30
#define TDO 250
#define T7 1600
#define WLK 2
#define WLV 4
#define PRE 3
#define TDK (2 * TDV)
#define WLO 1

constexpr int ACC_WORDS = 1792 * 2;
__device__ __align__(1024) unsigned long long g_acc[ACC_WORDS];
__device__ float g_side[ACC_WORDS];

#define GT_AT(n)
#define GT_END()

__device__ __forceinline__ void mbar_init(uint32_t bar, uint32_t cnt) {
    asm volatile("mbarrier.init.shared::cta.b64 [%0], %1;" ::"r"(bar), "r"(cnt) : "memory");
}
__device__ __forceinline__ void mbar_expect_tx(uint32_t bar, uint32_t bytes) {
    asm volatile("mbarrier.arrive.expect_tx.shared::cta.b64 _, [%0], %1;" ::"r"(bar), "r"(bytes) : "memory");
}
__device__ __forceinline__ void slot_release(uint32_t bar, uint32_t dep, uint32_t zero, int lane) {
    if (lane == 0) asm volatile("mbarrier.arrive.shared::cta.b64 _, [%0];" ::"r"(bar + (dep & zero)) : "memory");
}
__device__ __forceinline__ void mbar_wait_n(uint32_t bar, uint32_t& n) {
    asm volatile("{\n.reg .pred p, q;\n"
                 "WAIT_LOOP:\n"
                 "mbarrier.try_wait.parity.shared::cta.b64 p, [%1], 0;\n"
                 "add.u32 %0, %0, 1;\n"
                 "setp.lt.and.u32 q, %0, %2, !p;\n"
                 "@q bra.uni WAIT_LOOP;\n}"
                 : "+r"(n) : "r"(bar), "n"(SPIN_LIMIT) : "memory");
}
#define mbar_wait(bar) mbar_wait_n(bar, spins)
__device__ __forceinline__ void mbar_wait_fast(uint32_t bar) {
    asm volatile("{\n.reg .pred p;\nWAIT_LOOP:\nmbarrier.try_wait.parity.shared::cta.b64 p, [%0], 0;\n@!p bra.uni WAIT_LOOP;\n}"
                 ::"r"(bar) : "memory");
}
__device__ __forceinline__ uint32_t now_ns() {
    uint32_t t;
    asm volatile("mov.u32 %0, %%globaltimer_lo;" : "=r"(t)::"memory");
    return t;
}
__device__ __forceinline__ void pace(uint32_t due, uint32_t bar) {
    while ((int)(now_ns() - due) < 0) {
        uint32_t ok;
        asm volatile("{\n.reg .pred p;\nmbarrier.test_wait.parity.shared::cta.b64 p, [%1], 0;\nselp.u32 %0, 1, 0, p;\n}"
                     : "=r"(ok) : "r"(bar) : "memory");
        if (ok) break;
    }
}
__device__ __forceinline__ void bulk_g2s(uint32_t dst, const void* src, uint32_t bytes, uint32_t bar) {
    asm volatile("cp.async.bulk.shared::cluster.global.mbarrier::complete_tx::bytes [%0], [%1], %2, [%3];"
                 ::"r"(dst), "l"(src), "r"(bytes), "r"(bar) : "memory");
}
__device__ __forceinline__ void bulk_g2s_mc(uint32_t dst, const void* src, uint32_t bytes, uint32_t bar, uint16_t mask) {
    asm volatile("cp.async.bulk.shared::cluster.global.mbarrier::complete_tx::bytes.multicast::cluster [%0], [%1], %2, [%3], %4;"
                 ::"r"(dst), "l"(src), "r"(bytes), "r"(bar), "h"(mask) : "memory");
}
__device__ __forceinline__ void tma2d(uint32_t dst, const CUtensorMap* tm, int c0, int c1, uint32_t bar) {
    asm volatile("cp.async.bulk.tensor.2d.shared::cluster.global.mbarrier::complete_tx::bytes [%0], [%1, {%3, %4}], [%2];"
                 ::"r"(dst), "l"(tm), "r"(bar), "r"(c0), "r"(c1) : "memory");
}
__device__ __forceinline__ void tma3d(uint32_t dst, const CUtensorMap* tm, int c1, uint32_t bar) {
    asm volatile("cp.async.bulk.tensor.3d.shared::cluster.global.mbarrier::complete_tx::bytes [%0], [%1, {%3, %4, %3}], [%2];"
                 ::"r"(dst), "l"(tm), "r"(bar), "r"(0), "r"(c1) : "memory");
}
__device__ __forceinline__ uint32_t pin(uint32_t v) {
    uint32_t o;
    asm volatile("shfl.sync.bfly.b32 %0, %1, 0, 0x1f, 0xffffffff;" : "=r"(o) : "r"(v));
    return o;
}
template <typename T> __device__ __forceinline__ T* pin_ptr(T* p) {
    const unsigned long long a = (unsigned long long)p;
    return (T*)(((unsigned long long)pin((uint32_t)(a >> 32)) << 32) | pin((uint32_t)a));
}
__device__ __forceinline__ bool elect_one() {
    uint32_t p;
    asm volatile("{\n.reg .pred P;\nelect.sync _|P, 0xffffffff;\nselp.u32 %0, 1, 0, P;\n}" : "=r"(p));
    return p != 0;
}
__device__ __forceinline__ void bar_compute() { asm volatile("bar.sync 1, 256;" ::: "memory"); }
__device__ __forceinline__ void cluster_arrive() { asm volatile("barrier.cluster.arrive.relaxed.aligned;" ::: "memory"); }
__device__ __forceinline__ void cluster_wait() { asm volatile("barrier.cluster.wait.aligned;" ::: "memory"); }
__device__ __forceinline__ void fence_mbar_init() { asm volatile("fence.mbarrier_init.release.cluster;" ::: "memory"); }
__device__ __forceinline__ uint32_t mapa(uint32_t a, uint32_t rank) {
    uint32_t o;
    asm("mapa.shared::cluster.u32 %0, %1, %2;" : "=r"(o) : "r"(a), "r"(rank));
    return o;
}
__device__ __forceinline__ void st_async128(uint32_t a, uint32_t x, uint32_t y, uint32_t z, uint32_t w, uint32_t bar) {
    asm volatile("st.async.shared::cluster.mbarrier::complete_tx::bytes.v4.b32 [%0], {%1,%2,%3,%4}, [%5];"
                 ::"r"(a), "r"(x), "r"(y), "r"(z), "r"(w), "r"(bar) : "memory");
}
__device__ __forceinline__ void st_async64(uint32_t a, uint32_t x, uint32_t y, uint32_t bar) {
    asm volatile("st.async.shared::cluster.mbarrier::complete_tx::bytes.v2.b32 [%0], {%1,%2}, [%3];"
                 ::"r"(a), "r"(x), "r"(y), "r"(bar) : "memory");
}
__device__ __forceinline__ void mma16816(float (&c)[4], const uint4& a, uint32_t b0, uint32_t b1) {
    asm volatile("mma.sync.aligned.m16n8k16.row.col.f32.bf16.bf16.f32 {%0,%1,%2,%3}, {%4,%5,%6,%7}, {%8,%9}, {%0,%1,%2,%3};"
                 : "+f"(c[0]), "+f"(c[1]), "+f"(c[2]), "+f"(c[3])
                 : "r"(a.x), "r"(a.y), "r"(a.z), "r"(a.w), "r"(b0), "r"(b1));
}
__device__ __forceinline__ uint4 lds128(uint32_t a) {
    uint4 v;
    asm volatile("ld.shared.v4.u32 {%0,%1,%2,%3}, [%4];" : "=r"(v.x), "=r"(v.y), "=r"(v.z), "=r"(v.w) : "r"(a) : "memory");
    return v;
}
__device__ __forceinline__ float4 lds128f(uint32_t a) {
    float4 v;
    asm volatile("ld.shared.v4.f32 {%0,%1,%2,%3}, [%4];" : "=f"(v.x), "=f"(v.y), "=f"(v.z), "=f"(v.w) : "r"(a) : "memory");
    return v;
}
__device__ __forceinline__ float2 lds64f(uint32_t a) {
    float2 v;
    asm volatile("ld.shared.v2.f32 {%0,%1}, [%2];" : "=f"(v.x), "=f"(v.y) : "r"(a) : "memory");
    return v;
}
__device__ __forceinline__ uint2 lds64(uint32_t a) {
    uint2 v;
    asm volatile("ld.shared.v2.u32 {%0,%1}, [%2];" : "=r"(v.x), "=r"(v.y) : "r"(a) : "memory");
    return v;
}
__device__ __forceinline__ uint32_t lds32(uint32_t a) {
    uint32_t v;
    asm volatile("ld.shared.u32 %0, [%1];" : "=r"(v) : "r"(a) : "memory");
    return v;
}
__device__ __forceinline__ float lds32f(uint32_t a) { return __uint_as_float(lds32(a)); }
__device__ __forceinline__ void sts128f(uint32_t a, float x, float y, float z, float w) {
    asm volatile("st.shared.v4.f32 [%0], {%1,%2,%3,%4};" ::"r"(a), "f"(x), "f"(y), "f"(z), "f"(w) : "memory");
}
__device__ __forceinline__ void sts32(uint32_t a, uint32_t v) {
    asm volatile("st.shared.u32 [%0], %1;" ::"r"(a), "r"(v) : "memory");
}
__device__ __forceinline__ void sts16(uint32_t a, unsigned short v) {
    asm volatile("st.shared.u16 [%0], %1;" ::"r"(a), "h"(v) : "memory");
}
__device__ __forceinline__ uint4 ldsm4t(uint32_t a) {
    uint4 v;
    asm volatile("ldmatrix.sync.aligned.m8n8.x4.trans.shared.b16 {%0,%1,%2,%3}, [%4];"
                 : "=r"(v.x), "=r"(v.y), "=r"(v.z), "=r"(v.w) : "r"(a) : "memory");
    return v;
}
__device__ __forceinline__ uint32_t pack_bf16(float lo, float hi) {
    uint32_t r;
    asm("cvt.rn.bf16x2.f32 %0, %1, %2;" : "=r"(r) : "f"(hi), "f"(lo));
    return r;
}
__device__ __forceinline__ float round_bf16(float v) { return __uint_as_float(pack_bf16(0.f, v) & 0xFFFF0000u); }
__device__ __forceinline__ float ex2(float x) {
    float y;
    asm("ex2.approx.ftz.f32 %0, %1;" : "=f"(y) : "f"(x));
    return y;
}
__device__ __forceinline__ uint32_t fu(float v) { return __float_as_uint(v); }

__device__ __forceinline__ float acc_value(unsigned long long tot) {
    return fmaf((float)(int)(uint32_t)(tot >> 32), 0x1p-24f, (float)((uint32_t)tot >> 10) * 0x1p-46f);
}
__device__ __noinline__ void finish_with_side(unsigned long long tot, unsigned long long* acc_p, __nv_bfloat16* out_p) {
    if ((tot & 31ull) != 16ull) return;
    __threadfence();
    const float side = atomicExch(&g_side[acc_p - g_acc], 0.0f);
    *out_p = __float2bfloat16(acc_value(tot) + side);
    *acc_p = 0ull;
}
__device__ __noinline__ void accumulate_slow(float sum, unsigned long long* acc_p, __nv_bfloat16* out_p) {
    atomicAdd(&g_side[acc_p - g_acc], sum);
    __threadfence();
    finish_with_side(atomicAdd(acc_p, 33ull) + 33ull, acc_p, out_p);
}

__global__ void __launch_bounds__(NTHREADS, 2)
decode_kernel(const __nv_bfloat16* __restrict__ x, const __nv_bfloat16* __restrict__ kc,
              const __nv_bfloat16* __restrict__ wq, __nv_bfloat16* __restrict__ out,
              unsigned long long* __restrict__ acc, const uint32_t zero,
              const __grid_constant__ CUtensorMap wq_map, const __grid_constant__ CUtensorMap wo_map,
              const __grid_constant__ CUtensorMap v_map) {
    asm volatile("prefetch.global.L2 [%0];" ::"l"((const char*)wq + (blockIdx.x * 224 + min(threadIdx.x, 223u)) * 128));

    extern __shared__ __align__(1024) unsigned char smem[];
    const uint32_t sb = (uint32_t)__cvta_generic_to_shared(smem);
    const int warp = threadIdx.x >> 5, lane = threadIdx.x & 31;
    const int cta = blockIdx.x;
    const int gk = cta >> 4, r = cta & 15, b = r >> 2, s = r & 3;
    const bool proj = r < 14;
    const int c = r - 7 * (r >= 7);
    const uint32_t qfull = sb + OFF_BAR, kfull = qfull + 8, vfull = kfull + 64, ofull = vfull + 128, empty = ofull + 32;
    const uint32_t qbar = empty + 14 * 8, stbar = qbar + 8, obar = qbar + 16, hbar = qbar + 24, done = qbar + 56;
    uint32_t spins = 0;

    if (warp == 0) {
        const bool leader = elect_one();
        if (leader) {
            mbar_init(qfull, 1);
            mbar_expect_tx(qfull, 28672 + 3584);
            tma2d(sb, &wq_map, (cta >> 1) * 64, (cta & 1) * 224, qfull);
            fence_mbar_init();
        }
        uint32_t due = now_ns() + TK0 - (gk == 7 ? T7 : 0);
        __syncwarp();
        cluster_arrive();
        cluster_wait();
        if (leader) {
            if (proj) bulk_g2s_mc(sb + OFF_OB + r * 256, (const char*)x + r * 256, 256, qfull, (uint16_t)0xFFFF);
            int row = (b * 8 + gk) * SK + WIN0 + s * 256;
            const char* kp = (const char*)kc + (size_t)row * 512;
            uint32_t bar = kfull, dst = sb + 2 * SLOT;
#pragma unroll 1
            for (int i = 0; i < 8; i++) {
                mbar_expect_tx(bar, 16384);
                if (i >= 4) mbar_wait(empty + 8 * (i - 4));
                pace(due, i < WLK ? qfull : bar - 8 * WLK);
                bulk_g2s(dst, kp, 16384, bar);
                if (i == 1) {
                    asm volatile("prefetch.tensormap [%0];" ::"l"(&v_map) : "memory");
                    asm volatile("prefetch.tensormap [%0];" ::"l"(&wo_map) : "memory");
                }
                due += TDK;
                kp += 16384;
                bar += 8;
                dst = (i == 3) ? sb : dst + SLOT;
            }
#pragma unroll 1
            for (int k = 0; k < 16; k++) {
                mbar_expect_tx(bar, 8192);
                mbar_wait(empty + 8 * (4 + (k >> 1)));
                const int d = k - WLV;
                pace(due, vfull + 8 * (d < 0 ? (d >> 1) : d));
                tma3d(dst, &v_map, row, bar);
                due += TDV;
                row += 16;
                bar += 8;
                dst = (k == 3) ? sb : dst + 8192;
            }
            if (proj) {
                due += TGAP;
                mbar_wait(empty + 8 * 12);
                mbar_wait(empty + 8 * 13);
#pragma unroll 1
                for (int n = 0; n < 4; n++) {
                    mbar_expect_tx(bar, 8192);
                    pace(due, bar - 8 * WLO);
                    tma2d(sb + n * 8192, &wo_map, c * 64, (2 * gk + (r >= 7)) * 256 + n * 64, bar);
                    due += TDO;
                    bar += 8;
                }
            }
            mbar_wait(done);
            if (spins >= SPIN_LIMIT) __trap();
        }
        return;
    }

    const int w = warp - 1, j = threadIdx.x - 32;
    const int g = lane >> 2, t = lane & 3;

    if (w < 7) {
        cluster_arrive();
        cluster_wait();
        const uint32_t qa = sb + (w * 32 + (lane >> 4) * 8 + (lane & 7)) * 128;
        const uint32_t xa = sb + OFF_OB + (g & 3) * 896 + (cta & 1) * 448 + w * 64 + t * 4;
        mbar_wait(qfull);
        const uint32_t x0 = lds32(xa), x1 = lds32(xa + 16), x2 = lds32(xa + 32), x3 = lds32(xa + 48);
        float cq[4][4];
#pragma unroll
        for (int m = 0; m < 4; m++) {
            const uint32_t a = qa + (((2 * m + ((lane >> 3) & 1)) ^ (lane & 7)) << 4);
            const uint4 f0 = ldsm4t(a), f1 = ldsm4t(a + 2048);
            cq[m][0] = cq[m][1] = cq[m][2] = cq[m][3] = 0.f;
            mma16816(cq[m], f0, x0, x1);
            mma16816(cq[m], f1, x2, x3);
        }
        slot_release(empty + 8 * (w >> 2), fu(cq[0][0]) ^ fu(cq[1][0]) ^ fu(cq[2][0]) ^ fu(cq[3][0]), zero, lane);
        const int hf = t >> 1;
        const uint32_t qr = sb + OFF_QRED + w * 1024 + (t & 1) * 512 + hf * 128 + g * 16;
        sts128f(qr, hf ? cq[0][2] : cq[0][0], hf ? cq[1][2] : cq[1][0], hf ? cq[2][2] : cq[2][0], hf ? cq[3][2] : cq[3][0]);
        sts128f(qr + 256, hf ? cq[0][3] : cq[0][1], hf ? cq[1][3] : cq[1][1], hf ? cq[2][3] : cq[2][1], hf ? cq[3][3] : cq[3][1]);
    } else {
        if (lane == 0) {
#pragma unroll
            for (int i = 0; i < 28; i++) mbar_init(kfull + 8 * i, 1);
#pragma unroll
            for (int i = 0; i < 14; i++) mbar_init(empty + 8 * i, i == 1 ? 3 : (i < 10 ? 4 : 8));
#pragma unroll
            for (int i = 0; i < 7; i++) mbar_init(qbar + 8 * i, 1);
            mbar_init(done, 8);
            mbar_expect_tx(qbar, 4096);
            mbar_expect_tx(stbar, 64);
            mbar_expect_tx(obar, 2048);
#pragma unroll
            for (int i = 0; i < 4; i++) mbar_expect_tx(hbar + 8 * i, 512);
            fence_mbar_init();
        }
        __syncwarp();
        cluster_arrive();
        cluster_wait();
    }
    bar_compute();
    {
        const int pk = j >> 2;
        const uint32_t ra = sb + OFF_QRED + pk * 16;
        float4 a = lds128f(ra);
#pragma unroll
        for (int ww = 1; ww < 7; ww++) {
            const float4 v = lds128f(ra + ww * 1024);
            a.x += v.x; a.y += v.y; a.z += v.z; a.w += v.w;
        }
        const uint32_t dst = (pk >> 4) * 4 + (j & 3);
        st_async128(mapa(sb + OFF_QBUF + (r & 1) * 2048 + (r >> 1) * 256 + (pk & 15) * 16, dst),
                    fu(a.x), fu(a.y), fu(a.z), fu(a.w), mapa(qbar, dst));
        mbar_wait(qbar);
        const uint32_t qb = sb + OFF_QBUF + (j >> 5) * 256 + (j & 7) * 32 + ((j >> 3) & 3) * 4;
        const float q0 = lds32f(qb) + lds32f(qb + 2048), q1 = lds32f(qb + 16) + lds32f(qb + 2064);
        sts32(sb + OFF_QS + ((j >> 5) & 3) * 256 + (j & 1) * 128 + (j >> 7) * 64 + ((j >> 2) & 3) * 16 + ((j >> 4) & 1) * 8 + ((j >> 1) & 1) * 4,
              pack_bf16(q0, q1));
    }
    bar_compute();

    float s0 = 0.f, s1 = 0.f;
    {
        uint2 qf[8];
        const uint32_t qa = sb + OFF_QS + (g >> 2) * 128 + (g & 1) * 64 + t * 16;
        const uint32_t qx = ((g >> 1) & 1) * 8;
#pragma unroll
        for (int i = 0; i < 8; i++) qf[i] = lds64(qa + (i >> 1) * 256 + (((i & 1) * 8) ^ qx));
        const uint32_t kx = (g & 1) * 64;
        const uint32_t krow = sb + ((w & 3) * 8 + g) * 512 + t * 16;
        const int src = (lane & 28) + (g & 1);
#pragma unroll 1
        for (int k = 0; k < 4; k++) {
            const int ch = 2 * k + (w >> 2);
            const uint32_t ka = krow + (ch >= 4 ? ch - 4 : ch + 2) * SLOT;
            mbar_wait(kfull + 8 * ch);
            float a0[4] = {0.f, 0.f, 0.f, 0.f}, a1[4] = {0.f, 0.f, 0.f, 0.f};
#pragma unroll
            for (int i = 0; i < 8; i += 2) {
                const uint4 r0 = lds128(ka + ((i * 64) ^ kx)), r1 = lds128(ka + (((i + 1) * 64) ^ kx));
                mma16816(a0, r0, qf[i].x, qf[i].y);
                mma16816(a1, r1, qf[i + 1].x, qf[i + 1].y);
            }
            const float e0 = __shfl_sync(0xffffffffu, a0[0] + a1[0], src) + __shfl_sync(0xffffffffu, a0[2] + a1[2], src + 2);
            const float e1 = __shfl_sync(0xffffffffu, a0[1] + a1[1], src) + __shfl_sync(0xffffffffu, a0[3] + a1[3], src + 2);
            slot_release(empty + 8 * (2 + ch), fu(e0), zero, lane);
            if (t == k) { s0 = e0; s1 = e1; }
        }
    }
    float Mown;
    {
        const float kscale = 0.0625f * 1.4426950408889634f;
        s0 = round_bf16(s0) * kscale;
        s1 = round_bf16(s1) * kscale;
        float m0 = s0, m1 = s1;
#pragma unroll
        for (int o = 16; o > 0; o >>= 1) {
            m0 = fmaxf(m0, __shfl_xor_sync(0xffffffffu, m0, o));
            m1 = fmaxf(m1, __shfl_xor_sync(0xffffffffu, m1, o));
        }
        if (lane < 2) sts32(sb + OFF_WST + (w * 2 + lane) * 4, fu(lane ? m1 : m0));
        bar_compute();
        const float4 u0 = lds128f(sb + OFF_WST), u1 = lds128f(sb + OFF_WST + 16), u2 = lds128f(sb + OFF_WST + 32), u3 = lds128f(sb + OFF_WST + 48);
        const float M0 = fmaxf(fmaxf(fmaxf(u0.x, u0.z), fmaxf(u1.x, u1.z)), fmaxf(fmaxf(u2.x, u2.z), fmaxf(u3.x, u3.z)));
        const float M1 = fmaxf(fmaxf(fmaxf(u0.y, u0.w), fmaxf(u1.y, u1.w)), fmaxf(fmaxf(u2.y, u2.w), fmaxf(u3.y, u3.w)));
        Mown = (t & 1) ? M1 : M0;
        const uint32_t p = pack_bf16(ex2(s0 - M0), ex2(s1 - M1));
        const uint32_t pa = sb + OFF_PS + (4 * t + (w >> 1)) * 64 + (g >> 1) * 8 + (w & 1) * 4 + (g & 1) * 2;
        sts16(pa, (unsigned short)(p & 0xFFFFu));
        sts16(pa + 32, (unsigned short)(p >> 16));
        float l0 = __uint_as_float(p << 16), l1 = __uint_as_float(p & 0xFFFF0000u);
#pragma unroll
        for (int o = 16; o > 0; o >>= 1) {
            l0 += __shfl_xor_sync(0xffffffffu, l0, o);
            l1 += __shfl_xor_sync(0xffffffffu, l1, o);
        }
        if (lane < 2) sts32(sb + OFF_WST + 64 + (w * 2 + lane) * 4, fu(lane ? l1 : l0));
        bar_compute();
        if (j < 4) {
            const float4 v0 = lds128f(sb + OFF_WST + 64), v1 = lds128f(sb + OFF_WST + 80), v2 = lds128f(sb + OFF_WST + 96), v3 = lds128f(sb + OFF_WST + 112);
            const float L0 = ((v0.x + v0.z) + (v1.x + v1.z)) + ((v2.x + v2.z) + (v3.x + v3.z));
            const float L1 = ((v0.y + v0.w) + (v1.y + v1.w)) + ((v2.y + v2.w) + (v3.y + v3.w));
            st_async128(mapa(sb + OFF_WST + 128 + s * 16, b * 4 + j), fu(M0), fu(L0), fu(M1), fu(L1), mapa(stbar, b * 4 + j));
        }
    }

    const uint32_t h1_dst = pin(mapa(sb + OFF_HOP + r * 128 + (t >> 1) * 64 + g * 8, (t & 1) * 8 + w));
    const uint32_t h1_bar = pin(mapa(hbar + 8 * b, (t & 1) * 8 + w));
    const uint32_t h2_grp = (w >> 2) * 4 + (lane >> 3);
    const uint32_t h2_rank = h2_grp < 7 ? (r >> 3) * 7 + h2_grp : 14 + (r >> 3);
    const uint32_t h2_dst = pin(mapa(sb + OFF_OB + (w & 3) * OB_STRIDE + (r & 7) * 64 + (lane & 3) * 16 + ((lane >> 2) & 1) * 8, h2_rank));
    const uint32_t h2_bar = pin(mapa(obar, h2_rank));
    const uint32_t h2_src = pin(sb + OFF_HOP + (w & 3) * 512 + (lane & 7) * 16);
    const uint32_t h2_wait = pin(hbar + 8 * (w & 3));
    const uint32_t bars = pin(obar);
    const uint32_t wo_src = pin(sb + (((lane >> 3) & 1) * 16 + (lane >> 4) * 8 + (lane & 7)) * 128 + ((w ^ (lane & 7)) << 4));
    const uint32_t ob_src = pin(sb + OFF_OB + (g & 3) * OB_STRIDE + (g >> 2) * 64 + t * 16);
    unsigned long long* acc_p = pin_ptr(acc + (c * 16 + (j >> 4)) * 32 + (j & 15));
    __nv_bfloat16* out_p = pin_ptr(out + (g & 3) * 448 + c * 64 + w * 8 + 2 * t + (g >> 2));
    const uint32_t k_one = pin(zero + 1u);
    const bool t_hi = pin(t >> 1) != 0, g_hi = pin(g >> 2) != 0, proj_on = pin(proj ? 1u : 0u) != 0;

    float acc0[4] = {0.f, 0.f, 0.f, 0.f}, acc1[4] = {0.f, 0.f, 0.f, 0.f};
    float wgt;
    {
        const uint32_t va0 = pin(sb + (w >> 1) * 2048 + ((lane >> 4) * 8 + (lane & 7)) * 128 + ((((w & 1) * 4 + ((lane >> 3) & 1)) ^ (lane & 7)) << 4));
        const uint32_t va1 = pin(va0 ^ 32);
        const uint32_t pa = pin(sb + OFF_PS + ((g >> 1) & 1) * 32 + t * 8);
        const uint32_t vb = bars - (obar - vfull);
#pragma unroll 1
        for (int k = 0; k < 8; k += 2) {
            const uint32_t so = (k < 4 ? k + 8 : k - 4) * 8192;
            const uint2 p0 = lds64(pa + k * 64), p1 = lds64(pa + k * 64 + 64);
            mbar_wait(vb + 8 * k);
            const uint4 f0 = ldsm4t(va0 + so), f1 = ldsm4t(va1 + so);
            mma16816(acc0, f0, p0.x, p0.y);
            mma16816(acc1, f1, p0.x, p0.y);
            mbar_wait(vb + 8 * k + 8);
            const uint4 f2 = ldsm4t(va0 + so + 8192), f3 = ldsm4t(va1 + so + 8192);
            mma16816(acc0, f2, p1.x, p1.y);
            mma16816(acc1, f3, p1.x, p1.y);
            slot_release(empty + 8 * (10 + (k >> 1)), fu(acc0[0]) ^ fu(acc1[0]), zero, lane);
        }
        uint2 pw[8];
#pragma unroll
        for (int k = 8; k < 16; k++) pw[k - 8] = lds64(pa + k * 64);
        {
            mbar_wait(stbar);
            const uint32_t sa = sb + OFF_WST + 128 + (t & 1) * 8;
            const float2 z0 = lds64f(sa), z1 = lds64f(sa + 16), z2 = lds64f(sa + 32), z3 = lds64f(sa + 48);
            const float mx = fmaxf(fmaxf(z0.x, z1.x), fmaxf(z2.x, z3.x));
            const float W = (ex2(z0.x - mx) * z0.y + ex2(z1.x - mx) * z1.y) + (ex2(z2.x - mx) * z2.y + ex2(z3.x - mx) * z3.y);
            wgt = __uint_as_float(pin(fu(__fdividef(ex2(Mown - mx), W))));
        }
        uint4 f0, f1;
#pragma unroll
        for (int k = 8; k < 16; k++) {
            mbar_wait_fast(vb + 8 * k);
            if (k == 15) GT_AT(1);
            const uint4 n0 = ldsm4t(va0 + (k - 4) * 8192), n1 = ldsm4t(va1 + (k - 4) * 8192);
            if (k > 8) {
                mma16816(acc0, f0, pw[k - 9].x, pw[k - 9].y);
                mma16816(acc1, f1, pw[k - 9].x, pw[k - 9].y);
            }
            f0 = n0; f1 = n1;
        }
        mma16816(acc0, f0, pw[7].x, pw[7].y);
        mma16816(acc1, f1, pw[7].x, pw[7].y);
    }
    st_async64(h1_dst, fu((t_hi ? acc1[0] : acc0[0]) * wgt), fu((t_hi ? acc1[2] : acc0[2]) * wgt), h1_bar);
    {
        mbar_wait_fast(h2_wait);
        const float4 v0 = lds128f(h2_src), v1 = lds128f(h2_src + 128), v2 = lds128f(h2_src + 256), v3 = lds128f(h2_src + 384);
        st_async64(h2_dst, pack_bf16((v0.x + v1.x) + (v2.x + v3.x), (v0.z + v1.z) + (v2.z + v3.z)),
                   pack_bf16((v0.y + v1.y) + (v2.y + v3.y), (v0.w + v1.w) + (v2.w + v3.w)), h2_bar);
    }
    if (!proj_on) {
        mbar_wait_fast(bars);
        slot_release(bars + (done - obar), 0u, 0u, lane);
        GT_END();
        return;
    }
    float sum;
    {
        const uint32_t ob = bars - (obar - ofull);
        float x0[4] = {0.f, 0.f, 0.f, 0.f}, x1[4] = {0.f, 0.f, 0.f, 0.f}, y0[4] = {0.f, 0.f, 0.f, 0.f}, y1[4] = {0.f, 0.f, 0.f, 0.f};
        uint4 bp[4], bq[4], oa[4];
#pragma unroll
        for (int n = 0; n < 4; n++) {
            if (n == PRE) {
                mbar_wait_fast(bars);
                GT_AT(5);
#pragma unroll
                for (int i = 0; i < 4; i++) oa[i] = lds128(ob_src + i * 128);
#pragma unroll
                for (int i = 0; i < PRE; i++) {
                    mma16816(x0, oa[i], bp[i].x, bp[i].y);
                    mma16816(y0, oa[i], bp[i].z, bp[i].w);
                    mma16816(x1, oa[i], bq[i].x, bq[i].y);
                    mma16816(y1, oa[i], bq[i].z, bq[i].w);
                }
            }
            mbar_wait_fast(ob + 8 * n);
            if (n == 3) GT_AT(4);
            bp[n] = ldsm4t(wo_src + n * 8192);
            bq[n] = ldsm4t(wo_src + n * 8192 + 4096);
            if (n > PRE) {
                mma16816(x0, oa[n - 1], bp[n - 1].x, bp[n - 1].y);
                mma16816(y0, oa[n - 1], bp[n - 1].z, bp[n - 1].w);
                mma16816(x1, oa[n - 1], bq[n - 1].x, bq[n - 1].y);
                mma16816(y1, oa[n - 1], bq[n - 1].z, bq[n - 1].w);
            }
        }
        mma16816(x0, oa[3], bp[3].x, bp[3].y);
        mma16816(y0, oa[3], bp[3].z, bp[3].w);
        mma16816(x1, oa[3], bq[3].x, bq[3].y);
        mma16816(y1, oa[3], bq[3].z, bq[3].w);
        float keep = x0[0] + y0[2], send = x0[1] + y0[3];
        if (g_hi) { send = x1[0] + y1[2]; keep = x1[1] + y1[3]; }
        sum = keep + __shfl_xor_sync(0xffffffffu, send, 16);
    }
    const uint32_t bits = fu(sum);
    const uint32_t sh = 129u - ((bits >> 23) & 0xFFu);
    const uint32_t smant = (((bits << 3) & 0x3FFFFF8u) | 0x4000000u) ^ (uint32_t)((int)bits >> 31);
    long long fx;
    asm("shr.s64 %0, %1, %2;" : "=l"(fx) : "l"((long long)((unsigned long long)smant << 32)), "r"(sh));
    const unsigned long long inc = ((unsigned long long)fx & 0xFFFFFFFF00000000ull) | (((uint32_t)fx & ~0x3FFu) | k_one);
    const bool fast = __any_sync(0xffffffffu, fabsf(sum) >= 0x1p-30f) && fabsf(sum) < 8.0f;
    GT_AT(7);
    unsigned long long tot = 0ull;
    asm volatile("{\n.reg .pred p;\nsetp.ne.u32 p, %3, 0;\n@p atom.relaxed.gpu.global.add.u64 %0, [%1], %2;\n}"
                 : "+l"(tot) : "l"(acc_p), "l"(inc), "r"((uint32_t)fast) : "memory");
    slot_release(bars + (done - obar), 0u, 0u, lane);
    if (!fast) { accumulate_slow(sum, acc_p, out_p); return; }
    tot += inc;
    const uint32_t cnt = (uint32_t)tot & 0x3FFu;
    asm volatile("{\n.reg .pred p;\nsetp.eq.u32 p, %3, 16;\n@p st.global.u16 [%0], %1;\n@p st.global.u64 [%2], 0;\n}"
                 ::"l"(out_p), "h"(__bfloat16_as_ushort(__float2bfloat16(acc_value(tot)))), "l"(acc_p), "r"(cnt) : "memory");
    if (cnt > 16u) finish_with_side(tot, acc_p, out_p);
    GT_END();
}

typedef CUresult (*EncodeFn)(CUtensorMap*, CUtensorMapDataType, cuuint32_t, void*, const cuuint64_t*, const cuuint64_t*,
                             const cuuint32_t*, const cuuint32_t*, CUtensorMapInterleave, CUtensorMapSwizzle,
                             CUtensorMapL2promotion, CUtensorMapFloatOOBfill);

}

extern "C" void kernel_launch(void* const* d_in, const int* in_sizes, int n_in, void* d_out, int out_size) {
    (void)in_sizes; (void)n_in; (void)out_size;
    static EncodeFn encode = nullptr;
    static void* acc = nullptr;
    if (!encode) {
        cudaDriverEntryPointQueryResult qr;
        cudaGetDriverEntryPoint("cuTensorMapEncodeTiled", (void**)&encode, cudaEnableDefault, &qr);
        cudaGetSymbolAddress(&acc, g_acc);
        cudaFuncSetAttribute(decode_kernel, cudaFuncAttributeMaxDynamicSharedMemorySize, SMEM_BYTES);
        cudaFuncSetAttribute(decode_kernel, cudaFuncAttributeNonPortableClusterSizeAllowed, 1);
    }
    const cuuint32_t estr[3] = {1, 1, 1};
    CUtensorMap wq_map, wo_map, v_map;
    {
        const cuuint64_t dim[2] = {4096, 448}, str[1] = {8192};
        const cuuint32_t box[2] = {64, 224};
        encode(&wq_map, CU_TENSOR_MAP_DATA_TYPE_BFLOAT16, 2, d_in[3], dim, str, box, estr, CU_TENSOR_MAP_INTERLEAVE_NONE,
               CU_TENSOR_MAP_SWIZZLE_128B, CU_TENSOR_MAP_L2_PROMOTION_NONE, CU_TENSOR_MAP_FLOAT_OOB_FILL_NONE);
    }
    {
        const cuuint64_t dim[2] = {448, 4096}, str[1] = {896};
        const cuuint32_t box[2] = {64, 64};
        encode(&wo_map, CU_TENSOR_MAP_DATA_TYPE_BFLOAT16, 2, d_in[4], dim, str, box, estr, CU_TENSOR_MAP_INTERLEAVE_NONE,
               CU_TENSOR_MAP_SWIZZLE_128B, CU_TENSOR_MAP_L2_PROMOTION_NONE, CU_TENSOR_MAP_FLOAT_OOB_FILL_NONE);
    }
    {
        const cuuint64_t dim[3] = {64, 4ull * 8 * SK, 4}, str[2] = {512, 128};
        const cuuint32_t box[3] = {64, 16, 4};
        encode(&v_map, CU_TENSOR_MAP_DATA_TYPE_BFLOAT16, 3, d_in[2], dim, str, box, estr, CU_TENSOR_MAP_INTERLEAVE_NONE,
               CU_TENSOR_MAP_SWIZZLE_128B, CU_TENSOR_MAP_L2_PROMOTION_NONE, CU_TENSOR_MAP_FLOAT_OOB_FILL_NONE);
    }
    cudaLaunchConfig_t cfg = {};
    cfg.gridDim = dim3(128);
    cfg.blockDim = dim3(NTHREADS);
    cfg.dynamicSmemBytes = SMEM_BYTES;
    cfg.stream = cudaStreamPerThread;
    cudaLaunchAttribute attr[2];
    attr[0].id = cudaLaunchAttributeClusterDimension;
    attr[0].val.clusterDim.x = 16; attr[0].val.clusterDim.y = 1; attr[0].val.clusterDim.z = 1;
    attr[1].id = cudaLaunchAttributeClusterSchedulingPolicyPreference;
    attr[1].val.clusterSchedulingPolicyPreference = cudaClusterSchedulingPolicyLoadBalancing;
    cfg.attrs = attr;
    cfg.numAttrs = 2;
    cudaLaunchKernelEx(&cfg, decode_kernel, (const __nv_bfloat16*)d_in[0], (const __nv_bfloat16*)d_in[1],
                       (const __nv_bfloat16*)d_in[3], (__nv_bfloat16*)d_out, (unsigned long long*)acc, 0u,
                       wq_map, wo_map, v_map);
}
```

```cpp
#include <cuda_runtime.h>
#include <cuda_bf16.h>
#include <cuda.h>
#include <stdint.h>

namespace {

constexpr int SK = 4096, WIN0 = 3072;
constexpr int SLOT = 16384;
constexpr int OFF_BAR  = 6 * SLOT;
constexpr int OFF_QBUF = OFF_BAR + 416;
constexpr int OFF_QS   = OFF_QBUF + 4096;
constexpr int OFF_WST  = OFF_QS + 1024;
constexpr int OB_STRIDE = 576;
constexpr int OFF_OB   = OFF_WST + 192;
constexpr int OFF_HOP  = OFF_OB + 4 * OB_STRIDE;
constexpr int OFF_QRED = OFF_HOP + 2048;
constexpr int OFF_PS   = OFF_QRED;
constexpr int SMEM_BYTES = OFF_QRED + 7 * 1024;
static_assert(SMEM_BYTES <= 115712, "two CTAs must fit on one SM");
constexpr int NTHREADS = 288;
constexpr int SPIN_LIMIT = 1 << 20;

#define TK0 420
#define TDV 348
#define TGAP 30
#define TDO 300
#define T7 1600
#define WLK 2
#define WLV 4
#define TDK 662
#define TDV2 270
#define WLO 1

constexpr int ACC_WORDS = 1792 * 2;
__device__ __align__(1024) unsigned long long g_acc[ACC_WORDS];
__device__ float g_side[ACC_WORDS];

#define GT_AT(n)
#define GT_END()

__device__ __forceinline__ void mbar_init(uint32_t bar, uint32_t cnt) {
    asm volatile("mbarrier.init.shared::cta.b64 [%0], %1;" ::"r"(bar), "r"(cnt) : "memory");
}
__device__ __forceinline__ void mbar_expect_tx(uint32_t bar, uint32_t bytes) {
    asm volatile("mbarrier.arrive.expect_tx.shared::cta.b64 _, [%0], %1;" ::"r"(bar), "r"(bytes) : "memory");
}
__device__ __forceinline__ void slot_release(uint32_t bar, uint32_t dep, uint32_t zero, int lane) {
    if (lane == 0) asm volatile("mbarrier.arrive.shared::cta.b64 _, [%0];" ::"r"(bar + (dep & zero)) : "memory");
}
__device__ __forceinline__ void mbar_wait_n(uint32_t bar, uint32_t& n) {
    asm volatile("{\n.reg .pred p, q;\n"
                 "WAIT_LOOP:\n"
                 "mbarrier.try_wait.parity.shared::cta.b64 p, [%1], 0;\n"
                 "add.u32 %0, %0, 1;\n"
                 "setp.lt.and.u32 q, %0, %2, !p;\n"
                 "@q bra.uni WAIT_LOOP;\n}"
                 : "+r"(n) : "r"(bar), "n"(SPIN_LIMIT) : "memory");
}
#define mbar_wait(bar) mbar_wait_n(bar, spins)
__device__ __forceinline__ void mbar_wait_fast(uint32_t bar) {
    asm volatile("{\n.reg .pred p;\nWAIT_LOOP:\nmbarrier.try_wait.parity.shared::cta.b64 p, [%0], 0;\n@!p bra.uni WAIT_LOOP;\n}"
                 ::"r"(bar) : "memory");
}
__device__ __forceinline__ uint32_t now_ns() {
    uint32_t t;
    asm volatile("mov.u32 %0, %%globaltimer_lo;" : "=r"(t)::"memory");
    return t;
}
__device__ __forceinline__ void pace(uint32_t due, uint32_t bar) {
    while ((int)(now_ns() - due) < 0) {
        uint32_t ok;
        asm volatile("{\n.reg .pred p;\nmbarrier.test_wait.parity.shared::cta.b64 p, [%1], 0;\nselp.u32 %0, 1, 0, p;\n}"
                     : "=r"(ok) : "r"(bar) : "memory");
        if (ok) break;
    }
}
__device__ __forceinline__ void bulk_g2s(uint32_t dst, const void* src, uint32_t bytes, uint32_t bar) {
    asm volatile("cp.async.bulk.shared::cluster.global.mbarrier::complete_tx::bytes [%0], [%1], %2, [%3];"
                 ::"r"(dst), "l"(src), "r"(bytes), "r"(bar) : "memory");
}
__device__ __forceinline__ void bulk_g2s_mc(uint32_t dst, const void* src, uint32_t bytes, uint32_t bar, uint16_t mask) {
    asm volatile("cp.async.bulk.shared::cluster.global.mbarrier::complete_tx::bytes.multicast::cluster [%0], [%1], %2, [%3], %4;"
                 ::"r"(dst), "l"(src), "r"(bytes), "r"(bar), "h"(mask) : "memory");
}
__device__ __forceinline__ void tma2d(uint32_t dst, const CUtensorMap* tm, int c0, int c1, uint32_t bar) {
    asm volatile("cp.async.bulk.tensor.2d.shared::cluster.global.mbarrier::complete_tx::bytes [%0], [%1, {%3, %4}], [%2];"
                 ::"r"(dst), "l"(tm), "r"(bar), "r"(c0), "r"(c1) : "memory");
}
__device__ __forceinline__ void tma3d(uint32_t dst, const CUtensorMap* tm, int c1, uint32_t bar) {
    asm volatile("cp.async.bulk.tensor.3d.shared::cluster.global.mbarrier::complete_tx::bytes [%0], [%1, {%3, %4, %3}], [%2];"
                 ::"r"(dst), "l"(tm), "r"(bar), "r"(0), "r"(c1) : "memory");
}
__device__ __forceinline__ uint32_t pin(uint32_t v) {
    uint32_t o;
    asm volatile("shfl.sync.bfly.b32 %0, %1, 0, 0x1f, 0xffffffff;" : "=r"(o) : "r"(v));
    return o;
}
template <typename T> __device__ __forceinline__ T* pin_ptr(T* p) {
    const unsigned long long a = (unsigned long long)p;
    return (T*)(((unsigned long long)pin((uint32_t)(a >> 32)) << 32) | pin((uint32_t)a));
}
__device__ __forceinline__ bool elect_one() {
    uint32_t p;
    asm volatile("{\n.reg .pred P;\nelect.sync _|P, 0xffffffff;\nselp.u32 %0, 1, 0, P;\n}" : "=r"(p));
    return p != 0;
}
__device__ __forceinline__ void bar_compute() { asm volatile("bar.sync 1, 256;" ::: "memory"); }
__device__ __forceinline__ void cluster_arrive() { asm volatile("barrier.cluster.arrive.relaxed.aligned;" ::: "memory"); }
__device__ __forceinline__ void cluster_wait() { asm volatile("barrier.cluster.wait.aligned;" ::: "memory"); }
__device__ __forceinline__ void fence_mbar_init() { asm volatile("fence.mbarrier_init.release.cluster;" ::: "memory"); }
__device__ __forceinline__ uint32_t mapa(uint32_t a, uint32_t rank) {
    uint32_t o;
    asm("mapa.shared::cluster.u32 %0, %1, %2;" : "=r"(o) : "r"(a), "r"(rank));
    return o;
}
__device__ __forceinline__ void st_async128(uint32_t a, uint32_t x, uint32_t y, uint32_t z, uint32_t w, uint32_t bar) {
    asm volatile("st.async.shared::cluster.mbarrier::complete_tx::bytes.v4.b32 [%0], {%1,%2,%3,%4}, [%5];"
                 ::"r"(a), "r"(x), "r"(y), "r"(z), "r"(w), "r"(bar) : "memory");
}
__device__ __forceinline__ void st_async64(uint32_t a, uint32_t x, uint32_t y, uint32_t bar) {
    asm volatile("st.async.shared::cluster.mbarrier::complete_tx::bytes.v2.b32 [%0], {%1,%2}, [%3];"
                 ::"r"(a), "r"(x), "r"(y), "r"(bar) : "memory");
}
__device__ __forceinline__ void mma16816(float (&c)[4], const uint4& a, uint32_t b0, uint32_t b1) {
    asm volatile("mma.sync.aligned.m16n8k16.row.col.f32.bf16.bf16.f32 {%0,%1,%2,%3}, {%4,%5,%6,%7}, {%8,%9}, {%0,%1,%2,%3};"
                 : "+f"(c[0]), "+f"(c[1]), "+f"(c[2]), "+f"(c[3])
                 : "r"(a.x), "r"(a.y), "r"(a.z), "r"(a.w), "r"(b0), "r"(b1));
}
__device__ __forceinline__ uint4 lds128(uint32_t a) {
    uint4 v;
    asm volatile("ld.shared.v4.u32 {%0,%1,%2,%3}, [%4];" : "=r"(v.x), "=r"(v.y), "=r"(v.z), "=r"(v.w) : "r"(a) : "memory");
    return v;
}
__device__ __forceinline__ float4 lds128f(uint32_t a) {
    float4 v;
    asm volatile("ld.shared.v4.f32 {%0,%1,%2,%3}, [%4];" : "=f"(v.x), "=f"(v.y), "=f"(v.z), "=f"(v.w) : "r"(a) : "memory");
    return v;
}
__device__ __forceinline__ float2 lds64f(uint32_t a) {
    float2 v;
    asm volatile("ld.shared.v2.f32 {%0,%1}, [%2];" : "=f"(v.x), "=f"(v.y) : "r"(a) : "memory");
    return v;
}
__device__ __forceinline__ uint2 lds64(uint32_t a) {
    uint2 v;
    asm volatile("ld.shared.v2.u32 {%0,%1}, [%2];" : "=r"(v.x), "=r"(v.y) : "r"(a) : "memory");
    return v;
}
__device__ __forceinline__ uint32_t lds32(uint32_t a) {
    uint32_t v;
    asm volatile("ld.shared.u32 %0, [%1];" : "=r"(v) : "r"(a) : "memory");
    return v;
}
__device__ __forceinline__ float lds32f(uint32_t a) { return __uint_as_float(lds32(a)); }
__device__ __forceinline__ void sts128f(uint32_t a, float x, float y, float z, float w) {
    asm volatile("st.shared.v4.f32 [%0], {%1,%2,%3,%4};" ::"r"(a), "f"(x), "f"(y), "f"(z), "f"(w) : "memory");
}
__device__ __forceinline__ void sts32(uint32_t a, uint32_t v) {
    asm volatile("st.shared.u32 [%0], %1;" ::"r"(a), "r"(v) : "memory");
}
__device__ __forceinline__ void sts16(uint32_t a, unsigned short v) {
    asm volatile("st.shared.u16 [%0], %1;" ::"r"(a), "h"(v) : "memory");
}
__device__ __forceinline__ uint4 ldsm4t(uint32_t a) {
    uint4 v;
    asm volatile("ldmatrix.sync.aligned.m8n8.x4.trans.shared.b16 {%0,%1,%2,%3}, [%4];"
                 : "=r"(v.x), "=r"(v.y), "=r"(v.z), "=r"(v.w) : "r"(a) : "memory");
    return v;
}
__device__ __forceinline__ uint32_t pack_bf16(float lo, float hi) {
    uint32_t r;
    asm("cvt.rn.bf16x2.f32 %0, %1, %2;" : "=r"(r) : "f"(hi), "f"(lo));
    return r;
}
__device__ __forceinline__ float round_bf16(float v) { return __uint_as_float(pack_bf16(0.f, v) & 0xFFFF0000u); }
__device__ __forceinline__ float ex2(float x) {
    float y;
    asm("ex2.approx.ftz.f32 %0, %1;" : "=f"(y) : "f"(x));
    return y;
}
__device__ __forceinline__ uint32_t fu(float v) { return __float_as_uint(v); }

__device__ __forceinline__ float acc_value(unsigned long long tot) {
    return fmaf((float)(int)(uint32_t)(tot >> 32), 0x1p-24f, (float)((uint32_t)tot >> 10) * 0x1p-46f);
}
__device__ __noinline__ void finish_with_side(unsigned long long tot, unsigned long long* acc_p, __nv_bfloat16* out_p) {
    if ((tot & 31ull) != 16ull) return;
    __threadfence();
    const float side = atomicExch(&g_side[acc_p - g_acc], 0.0f);
    *out_p = __float2bfloat16(acc_value(tot) + side);
    *acc_p = 0ull;
}
__device__ __noinline__ void accumulate_slow(float sum, unsigned long long* acc_p, __nv_bfloat16* out_p) {
    atomicAdd(&g_side[acc_p - g_acc], sum);
    __threadfence();
    finish_with_side(atomicAdd(acc_p, 33ull) + 33ull, acc_p, out_p);
}

__global__ void __launch_bounds__(NTHREADS, 2)
decode_kernel(const __nv_bfloat16* __restrict__ x, const __nv_bfloat16* __restrict__ kc,
              const __nv_bfloat16* __restrict__ wq, __nv_bfloat16* __restrict__ out,
              unsigned long long* __restrict__ acc, const uint32_t zero,
              const __grid_constant__ CUtensorMap wq_map, const __grid_constant__ CUtensorMap wo_map,
              const __grid_constant__ CUtensorMap v_map) {
    asm volatile("prefetch.global.L2 [%0];" ::"l"((const char*)wq + (blockIdx.x * 224 + min(threadIdx.x, 223u)) * 128));

    extern __shared__ __align__(1024) unsigned char smem[];
    const uint32_t sb = (uint32_t)__cvta_generic_to_shared(smem);
    const int warp = threadIdx.x >> 5, lane = threadIdx.x & 31;
    const int cta = blockIdx.x;
    const int gk = cta >> 4, r = cta & 15, b = r >> 2, s = r & 3;
    const bool proj = r < 14;
    const int c = r - 7 * (r >= 7);
    const uint32_t qfull = sb + OFF_BAR, kfull = qfull + 8, vfull = kfull + 64, ofull = vfull + 128, empty = ofull + 32;
    const uint32_t qbar = empty + 14 * 8, stbar = qbar + 8, obar = qbar + 16, hbar = qbar + 24, done = qbar + 56;
    uint32_t spins = 0;

    if (warp == 0) {
        const bool leader = elect_one();
        if (leader) {
            mbar_init(qfull, 1);
            mbar_expect_tx(qfull, 28672 + 3584);
            tma2d(sb, &wq_map, (cta >> 1) * 64, (cta & 1) * 224, qfull);
            fence_mbar_init();
        }
        uint32_t due = now_ns() + TK0 - (gk == 7 ? T7 : 0);
        __syncwarp();
        cluster_arrive();
        cluster_wait();
        if (leader) {
            if (proj) bulk_g2s_mc(sb + OFF_OB + r * 256, (const char*)x + r * 256, 256, qfull, (uint16_t)0xFFFF);
            int row = (b * 8 + gk) * SK + WIN0 + s * 256;
            const char* kp = (const char*)kc + (size_t)row * 512;
            uint32_t bar = kfull, dst = sb + 2 * SLOT;
#pragma unroll 1
            for (int i = 0; i < 8; i++) {
                mbar_expect_tx(bar, 16384);
                if (i >= 4) mbar_wait(empty + 8 * (i - 4));
                pace(due, i < WLK ? qfull : bar - 8 * WLK);
                bulk_g2s(dst, kp, 16384, bar);
                if (i == 1) {
                    asm volatile("prefetch.tensormap [%0];" ::"l"(&v_map) : "memory");
                    asm volatile("prefetch.tensormap [%0];" ::"l"(&wo_map) : "memory");
                }
                due += TDK;
                kp += 16384;
                bar += 8;
                dst = (i == 3) ? sb : dst + SLOT;
            }
#pragma unroll 1
            for (int k = 0; k < 16; k++) {
                mbar_expect_tx(bar, 8192);
                mbar_wait(empty + 8 * (4 + (k >> 1)));
                const int d = k - WLV;
                pace(due, vfull + 8 * (d < 0 ? (d >> 1) : d));
                tma3d(dst, &v_map, row, bar);
                due += k < 12 ? TDV : TDV2;
                row += 16;
                bar += 8;
                dst = (k == 3) ? sb : dst + 8192;
            }
            if (proj) {
                due += TGAP;
                mbar_wait(empty + 8 * 12);
                mbar_wait(empty + 8 * 13);
#pragma unroll 1
                for (int n = 0; n < 4; n++) {
                    mbar_expect_tx(bar, 8192);
                    pace(due, bar - 8 * WLO);
                    tma2d(sb + n * 8192, &wo_map, c * 64, (2 * gk + (r >= 7)) * 256 + n * 64, bar);
                    due += TDO;
                    bar += 8;
                }
            }
            mbar_wait(done);
            if (spins >= SPIN_LIMIT) __trap();
        }
        return;
    }

    const int w = warp - 1, j = threadIdx.x - 32;
    const int g = lane >> 2, t = lane & 3;

    if (w < 7) {
        cluster_arrive();
        cluster_wait();
        const uint32_t qa = sb + (w * 32 + (lane >> 4) * 8 + (lane & 7)) * 128;
        const uint32_t xa = sb + OFF_OB + (g & 3) * 896 + (cta & 1) * 448 + w * 64 + t * 4;
        mbar_wait(qfull);
        const uint32_t x0 = lds32(xa), x1 = lds32(xa + 16), x2 = lds32(xa + 32), x3 = lds32(xa + 48);
        float cq[4][4];
#pragma unroll
        for (int m = 0; m < 4; m++) {
            const uint32_t a = qa + (((2 * m + ((lane >> 3) & 1)) ^ (lane & 7)) << 4);
            const uint4 f0 = ldsm4t(a), f1 = ldsm4t(a + 2048);
            cq[m][0] = cq[m][1] = cq[m][2] = cq[m][3] = 0.f;
            mma16816(cq[m], f0, x0, x1);
            mma16816(cq[m], f1, x2, x3);
        }
        slot_release(empty + 8 * (w >> 2), fu(cq[0][0]) ^ fu(cq[1][0]) ^ fu(cq[2][0]) ^ fu(cq[3][0]), zero, lane);
        const int hf = t >> 1;
        const uint32_t qr = sb + OFF_QRED + w * 1024 + (t & 1) * 512 + hf * 128 + g * 16;
        sts128f(qr, hf ? cq[0][2] : cq[0][0], hf ? cq[1][2] : cq[1][0], hf ? cq[2][2] : cq[2][0], hf ? cq[3][2] : cq[3][0]);
        sts128f(qr + 256, hf ? cq[0][3] : cq[0][1], hf ? cq[1][3] : cq[1][1], hf ? cq[2][3] : cq[2][1], hf ? cq[3][3] : cq[3][1]);
    } else {
        if (lane == 0) {
#pragma unroll
            for (int i = 0; i < 28; i++) mbar_init(kfull + 8 * i, 1);
#pragma unroll
            for (int i = 0; i < 14; i++) mbar_init(empty + 8 * i, i == 1 ? 3 : (i < 10 ? 4 : 8));
#pragma unroll
            for (int i = 0; i < 7; i++) mbar_init(qbar + 8 * i, 1);
            mbar_init(done, 8);
            mbar_expect_tx(qbar, 4096);
            mbar_expect_tx(stbar, 64);
            mbar_expect_tx(obar, 2048);
#pragma unroll
            for (int i = 0; i < 4; i++) mbar_expect_tx(hbar + 8 * i, 512);
            fence_mbar_init();
        }
        __syncwarp();
        cluster_arrive();
        cluster_wait();
    }
    bar_compute();
    {
        const int pk = j >> 2;
        const uint32_t ra = sb + OFF_QRED + pk * 16;
        float4 a = lds128f(ra);
#pragma unroll
        for (int ww = 1; ww < 7; ww++) {
            const float4 v = lds128f(ra + ww * 1024);
            a.x += v.x; a.y += v.y; a.z += v.z; a.w += v.w;
        }
        const uint32_t dst = (pk >> 4) * 4 + (j & 3);
        st_async128(mapa(sb + OFF_QBUF + (r & 1) * 2048 + (r >> 1) * 256 + (pk & 15) * 16, dst),
                    fu(a.x), fu(a.y), fu(a.z), fu(a.w), mapa(qbar, dst));
        mbar_wait(qbar);
        const uint32_t qb = sb + OFF_QBUF + (j >> 5) * 256 + (j & 7) * 32 + ((j >> 3) & 3) * 4;
        const float q0 = lds32f(qb) + lds32f(qb + 2048), q1 = lds32f(qb + 16) + lds32f(qb + 2064);
        sts32(sb + OFF_QS + ((j >> 5) & 3) * 256 + (j & 1) * 128 + (j >> 7) * 64 + ((j >> 2) & 3) * 16 + ((j >> 4) & 1) * 8 + ((j >> 1) & 1) * 4,
              pack_bf16(q0, q1));
    }
    bar_compute();

    float s0 = 0.f, s1 = 0.f;
    {
        uint2 qf[8];
        const uint32_t qa = sb + OFF_QS + (g >> 2) * 128 + (g & 1) * 64 + t * 16;
        const uint32_t qx = ((g >> 1) & 1) * 8;
#pragma unroll
        for (int i = 0; i < 8; i++) qf[i] = lds64(qa + (i >> 1) * 256 + (((i & 1) * 8) ^ qx));
        const uint32_t kx = (g & 1) * 64;
        const uint32_t krow = sb + ((w & 3) * 8 + g) * 512 + t * 16;
        const int src = (lane & 28) + (g & 1);
#pragma unroll 1
        for (int k = 0; k < 4; k++) {
            const int ch = 2 * k + (w >> 2);
            const uint32_t ka = krow + (ch >= 4 ? ch - 4 : ch + 2) * SLOT;
            mbar_wait(kfull + 8 * ch);
            float a0[4] = {0.f, 0.f, 0.f, 0.f}, a1[4] = {0.f, 0.f, 0.f, 0.f};
#pragma unroll
            for (int i = 0; i < 8; i += 2) {
                const uint4 r0 = lds128(ka + ((i * 64) ^ kx)), r1 = lds128(ka + (((i + 1) * 64) ^ kx));
                mma16816(a0, r0, qf[i].x, qf[i].y);
                mma16816(a1, r1, qf[i + 1].x, qf[i + 1].y);
            }
            const float e0 = __shfl_sync(0xffffffffu, a0[0] + a1[0], src) + __shfl_sync(0xffffffffu, a0[2] + a1[2], src + 2);
            const float e1 = __shfl_sync(0xffffffffu, a0[1] + a1[1], src) + __shfl_sync(0xffffffffu, a0[3] + a1[3], src + 2);
            slot_release(empty + 8 * (2 + ch), fu(e0), zero, lane);
            if (t == k) { s0 = e0; s1 = e1; }
        }
    }
    float Mown;
    {
        const float kscale = 0.0625f * 1.4426950408889634f;
        s0 = round_bf16(s0) * kscale;
        s1 = round_bf16(s1) * kscale;
        float m0 = s0, m1 = s1;
#pragma unroll
        for (int o = 16; o > 0; o >>= 1) {
            m0 = fmaxf(m0, __shfl_xor_sync(0xffffffffu, m0, o));
            m1 = fmaxf(m1, __shfl_xor_sync(0xffffffffu, m1, o));
        }
        if (lane < 2) sts32(sb + OFF_WST + (w * 2 + lane) * 4, fu(lane ? m1 : m0));
        bar_compute();
        const float4 u0 = lds128f(sb + OFF_WST), u1 = lds128f(sb + OFF_WST + 16), u2 = lds128f(sb + OFF_WST + 32), u3 = lds128f(sb + OFF_WST + 48);
        const float M0 = fmaxf(fmaxf(fmaxf(u0.x, u0.z), fmaxf(u1.x, u1.z)), fmaxf(fmaxf(u2.x, u2.z), fmaxf(u3.x, u3.z)));
        const float M1 = fmaxf(fmaxf(fmaxf(u0.y, u0.w), fmaxf(u1.y, u1.w)), fmaxf(fmaxf(u2.y, u2.w), fmaxf(u3.y, u3.w)));
        Mown = (t & 1) ? M1 : M0;
        const uint32_t p = pack_bf16(ex2(s0 - M0), ex2(s1 - M1));
        const uint32_t pa = sb + OFF_PS + (4 * t + (w >> 1)) * 64 + (g >> 1) * 8 + (w & 1) * 4 + (g & 1) * 2;
        sts16(pa, (unsigned short)(p & 0xFFFFu));
        sts16(pa + 32, (unsigned short)(p >> 16));
        float l0 = __uint_as_float(p << 16), l1 = __uint_as_float(p & 0xFFFF0000u);
#pragma unroll
        for (int o = 16; o > 0; o >>= 1) {
            l0 += __shfl_xor_sync(0xffffffffu, l0, o);
            l1 += __shfl_xor_sync(0xffffffffu, l1, o);
        }
        if (lane < 2) sts32(sb + OFF_WST + 64 + (w * 2 + lane) * 4, fu(lane ? l1 : l0));
        bar_compute();
        if (j < 4) {
            const float4 v0 = lds128f(sb + OFF_WST + 64), v1 = lds128f(sb + OFF_WST + 80), v2 = lds128f(sb + OFF_WST + 96), v3 = lds128f(sb + OFF_WST + 112);
            const float L0 = ((v0.x + v0.z) + (v1.x + v1.z)) + ((v2.x + v2.z) + (v3.x + v3.z));
            const float L1 = ((v0.y + v0.w) + (v1.y + v1.w)) + ((v2.y + v2.w) + (v3.y + v3.w));
            st_async128(mapa(sb + OFF_WST + 128 + s * 16, b * 4 + j), fu(M0), fu(L0), fu(M1), fu(L1), mapa(stbar, b * 4 + j));
        }
    }

    const uint32_t h1_dst = pin(mapa(sb + OFF_HOP + r * 128 + (t >> 1) * 64 + g * 8, (t & 1) * 8 + w));
    const uint32_t h1_bar = pin(mapa(hbar + 8 * b, (t & 1) * 8 + w));
    const uint32_t h2_grp = (w >> 2) * 4 + (lane >> 3);
    const uint32_t h2_rank = h2_grp < 7 ? (r >> 3) * 7 + h2_grp : 14 + (r >> 3);
    const uint32_t h2_dst = pin(mapa(sb + OFF_OB + (w & 3) * OB_STRIDE + (r & 7) * 64 + (lane & 3) * 16 + ((lane >> 2) & 1) * 8, h2_rank));
    const uint32_t h2_bar = pin(mapa(obar, h2_rank));
    const uint32_t h2_src = pin(sb + OFF_HOP + (w & 3) * 512 + (lane & 7) * 16);
    const uint32_t h2_wait = pin(hbar + 8 * (w & 3));
    const uint32_t bars = pin(obar);
    const uint32_t wo_src = pin(sb + (((lane >> 3) & 1) * 16 + (lane >> 4) * 8 + (lane & 7)) * 128 + ((w ^ (lane & 7)) << 4));
    const uint32_t ob_src = pin(sb + OFF_OB + (g & 3) * OB_STRIDE + (g >> 2) * 64 + t * 16);
    unsigned long long* acc_p = pin_ptr(acc + (c * 16 + (j >> 4)) * 32 + (j & 15));
    __nv_bfloat16* out_p = pin_ptr(out + (g & 3) * 448 + c * 64 + w * 8 + 2 * t + (g >> 2));
    const uint32_t k_one = pin(zero + 1u);
    const bool t_hi = pin(t >> 1) != 0, g_hi = pin(g >> 2) != 0, proj_on = pin(proj ? 1u : 0u) != 0;

    float acc0[4] = {0.f, 0.f, 0.f, 0.f}, acc1[4] = {0.f, 0.f, 0.f, 0.f};
    float wgt;
    {
        const uint32_t va0 = pin(sb + (w >> 1) * 2048 + ((lane >> 4) * 8 + (lane & 7)) * 128 + ((((w & 1) * 4 + ((lane >> 3) & 1)) ^ (lane & 7)) << 4));
        const uint32_t va1 = pin(va0 ^ 32);
        const uint32_t pa = pin(sb + OFF_PS + ((g >> 1) & 1) * 32 + t * 8);
        const uint32_t vb = bars - (obar - vfull);
#pragma unroll 1
        for (int k = 0; k < 8; k += 2) {
            const uint32_t so = (k < 4 ? k + 8 : k - 4) * 8192;
            const uint2 p0 = lds64(pa + k * 64), p1 = lds64(pa + k * 64 + 64);
            mbar_wait(vb + 8 * k);
            const uint4 f0 = ldsm4t(va0 + so), f1 = ldsm4t(va1 + so);
            mma16816(acc0, f0, p0.x, p0.y);
            mma16816(acc1, f1, p0.x, p0.y);
            mbar_wait(vb + 8 * k + 8);
            const uint4 f2 = ldsm4t(va0 + so + 8192), f3 = ldsm4t(va1 + so + 8192);
            mma16816(acc0, f2, p1.x, p1.y);
            mma16816(acc1, f3, p1.x, p1.y);
            slot_release(empty + 8 * (10 + (k >> 1)), fu(acc0[0]) ^ fu(acc1[0]), zero, lane);
        }
        uint2 pw[8];
#pragma unroll
        for (int k = 8; k < 16; k++) pw[k - 8] = lds64(pa + k * 64);
        {
            mbar_wait(stbar);
            const uint32_t sa = sb + OFF_WST + 128 + (t & 1) * 8;
            const float2 z0 = lds64f(sa), z1 = lds64f(sa + 16), z2 = lds64f(sa + 32), z3 = lds64f(sa + 48);
            const float mx = fmaxf(fmaxf(z0.x, z1.x), fmaxf(z2.x, z3.x));
            const float W = (ex2(z0.x - mx) * z0.y + ex2(z1.x - mx) * z1.y) + (ex2(z2.x - mx) * z2.y + ex2(z3.x - mx) * z3.y);
            wgt = __uint_as_float(pin(fu(__fdividef(ex2(Mown - mx), W))));
        }
        uint4 f0, f1;
#pragma unroll
        for (int k = 8; k < 16; k++) {
            mbar_wait_fast(vb + 8 * k);
            if (k == 15) GT_AT(1);
            const uint4 n0 = ldsm4t(va0 + (k - 4) * 8192), n1 = ldsm4t(va1 + (k - 4) * 8192);
            if (k > 8) {
                mma16816(acc0, f0, pw[k - 9].x, pw[k - 9].y);
                mma16816(acc1, f1, pw[k - 9].x, pw[k - 9].y);
            }
            f0 = n0; f1 = n1;
        }
        mma16816(acc0, f0, pw[7].x, pw[7].y);
        mma16816(acc1, f1, pw[7].x, pw[7].y);
    }
    st_async64(h1_dst, fu((t_hi ? acc1[0] : acc0[0]) * wgt), fu((t_hi ? acc1[2] : acc0[2]) * wgt), h1_bar);
    {
        mbar_wait_fast(h2_wait);
        const float4 v0 = lds128f(h2_src), v1 = lds128f(h2_src + 128), v2 = lds128f(h2_src + 256), v3 = lds128f(h2_src + 384);
        st_async64(h2_dst, pack_bf16((v0.x + v1.x) + (v2.x + v3.x), (v0.z + v1.z) + (v2.z + v3.z)),
                   pack_bf16((v0.y + v1.y) + (v2.y + v3.y), (v0.w + v1.w) + (v2.w + v3.w)), h2_bar);
    }
    if (!proj_on) {
        mbar_wait_fast(bars);
        slot_release(bars + (done - obar), 0u, 0u, lane);
        GT_END();
        return;
    }
    float sum;
    {
        const uint32_t ob = bars - (obar - ofull);
        float x0[4] = {0.f, 0.f, 0.f, 0.f}, x1[4] = {0.f, 0.f, 0.f, 0.f}, y0[4] = {0.f, 0.f, 0.f, 0.f}, y1[4] = {0.f, 0.f, 0.f, 0.f};
        uint4 bp[4], bq[4], oa[4];
#pragma unroll
        for (int n = 0; n < 3; n++) {
            mbar_wait_fast(ob + 8 * n);
            bp[n] = ldsm4t(wo_src + n * 8192);
            bq[n] = ldsm4t(wo_src + n * 8192 + 4096);
        }
        mbar_wait_fast(bars);
        GT_AT(5);
#pragma unroll
        for (int n = 0; n < 4; n++) oa[n] = lds128(ob_src + n * 128);
#pragma unroll
        for (int n = 0; n < 4; n++) {
            if (n == 3) {
                mbar_wait_fast(ob + 24);
                GT_AT(4);
                bp[3] = ldsm4t(wo_src + 3 * 8192);
                bq[3] = ldsm4t(wo_src + 3 * 8192 + 4096);
            }
            mma16816(x0, oa[n], bp[n].x, bp[n].y);
            mma16816(y0, oa[n], bp[n].z, bp[n].w);
            mma16816(x1, oa[n], bq[n].x, bq[n].y);
            mma16816(y1, oa[n], bq[n].z, bq[n].w);
        }
        float keep = x0[0] + y0[2], send = x0[1] + y0[3];
        if (g_hi) { send = x1[0] + y1[2]; keep = x1[1] + y1[3]; }
        sum = keep + __shfl_xor_sync(0xffffffffu, send, 16);
    }
    const uint32_t bits = fu(sum);
    const uint32_t sh = 129u - ((bits >> 23) & 0xFFu);
    const uint32_t smant = (((bits << 3) & 0x3FFFFF8u) | 0x4000000u) ^ (uint32_t)((int)bits >> 31);
    long long fx;
    asm("shr.s64 %0, %1, %2;" : "=l"(fx) : "l"((long long)((unsigned long long)smant << 32)), "r"(sh));
    const unsigned long long inc = ((unsigned long long)fx & 0xFFFFFFFF00000000ull) | (((uint32_t)fx & ~0x3FFu) | k_one);
    const bool fast = __any_sync(0xffffffffu, fabsf(sum) >= 0x1p-22f) && fabsf(sum) < 8.0f;
    GT_AT(7);
    unsigned long long tot = 0ull;
    asm volatile("{\n.reg .pred p;\nsetp.ne.u32 p, %3, 0;\n@p atom.relaxed.gpu.global.add.u64 %0, [%1], %2;\n}"
                 : "+l"(tot) : "l"(acc_p), "l"(inc), "r"((uint32_t)fast) : "memory");
    slot_release(bars + (done - obar), 0u, 0u, lane);
    if (!fast) { accumulate_slow(sum, acc_p, out_p); return; }
    tot += inc;
    const uint32_t cnt = (uint32_t)tot & 0x3FFu;
    asm volatile("{\n.reg .pred p;\nsetp.eq.u32 p, %3, 16;\n@p st.global.u16 [%0], %1;\n@p st.global.u64 [%2], 0;\n}"
                 ::"l"(out_p), "h"(__bfloat16_as_ushort(__float2bfloat16(acc_value(tot)))), "l"(acc_p), "r"(cnt) : "memory");
    if (cnt > 16u) finish_with_side(tot, acc_p, out_p);
    GT_END();
}

typedef CUresult (*EncodeFn)(CUtensorMap*, CUtensorMapDataType, cuuint32_t, void*, const cuuint64_t*, const cuuint64_t*,
                             const cuuint32_t*, const cuuint32_t*, CUtensorMapInterleave, CUtensorMapSwizzle,
                             CUtensorMapL2promotion, CUtensorMapFloatOOBfill);

}

extern "C" void kernel_launch(void* const* d_in, const int* in_sizes, int n_in, void* d_out, int out_size) {
    (void)in_sizes; (void)n_in; (void)out_size;
    static EncodeFn encode = nullptr;
    static void* acc = nullptr;
    if (!encode) {
        cudaDriverEntryPointQueryResult qr;
        cudaGetDriverEntryPoint("cuTensorMapEncodeTiled", (void**)&encode, cudaEnableDefault, &qr);
        cudaGetSymbolAddress(&acc, g_acc);
        cudaFuncSetAttribute(decode_kernel, cudaFuncAttributeMaxDynamicSharedMemorySize, SMEM_BYTES);
        cudaFuncSetAttribute(decode_kernel, cudaFuncAttributeNonPortableClusterSizeAllowed, 1);
    }
    const cuuint32_t estr[3] = {1, 1, 1};
    CUtensorMap wq_map, wo_map, v_map;
    {
        const cuuint64_t dim[2] = {4096, 448}, str[1] = {8192};
        const cuuint32_t box[2] = {64, 224};
        encode(&wq_map, CU_TENSOR_MAP_DATA_TYPE_BFLOAT16, 2, d_in[3], dim, str, box, estr, CU_TENSOR_MAP_INTERLEAVE_NONE,
               CU_TENSOR_MAP_SWIZZLE_128B, CU_TENSOR_MAP_L2_PROMOTION_NONE, CU_TENSOR_MAP_FLOAT_OOB_FILL_NONE);
    }
    {
        const cuuint64_t dim[2] = {448, 4096}, str[1] = {896};
        const cuuint32_t box[2] = {64, 64};
        encode(&wo_map, CU_TENSOR_MAP_DATA_TYPE_BFLOAT16, 2, d_in[4], dim, str, box, estr, CU_TENSOR_MAP_INTERLEAVE_NONE,
               CU_TENSOR_MAP_SWIZZLE_128B, CU_TENSOR_MAP_L2_PROMOTION_NONE, CU_TENSOR_MAP_FLOAT_OOB_FILL_NONE);
    }
    {
        const cuuint64_t dim[3] = {64, 4ull * 8 * SK, 4}, str[2] = {512, 128};
        const cuuint32_t box[3] = {64, 16, 4};
        encode(&v_map, CU_TENSOR_MAP_DATA_TYPE_BFLOAT16, 3, d_in[2], dim, str, box, estr, CU_TENSOR_MAP_INTERLEAVE_NONE,
               CU_TENSOR_MAP_SWIZZLE_128B, CU_TENSOR_MAP_L2_PROMOTION_NONE, CU_TENSOR_MAP_FLOAT_OOB_FILL_NONE);
    }
    cudaLaunchConfig_t cfg = {};
    cfg.gridDim = dim3(128);
    cfg.blockDim = dim3(NTHREADS);
    cfg.dynamicSmemBytes = SMEM_BYTES;
    cfg.stream = cudaStreamPerThread;
    cudaLaunchAttribute attr[2];
    attr[0].id = cudaLaunchAttributeClusterDimension;
    attr[0].val.clusterDim.x = 16; attr[0].val.clusterDim.y = 1; attr[0].val.clusterDim.z = 1;
    attr[1].id = cudaLaunchAttributeClusterSchedulingPolicyPreference;
    attr[1].val.clusterSchedulingPolicyPreference = cudaClusterSchedulingPolicyLoadBalancing;
    cfg.attrs = attr;
    cfg.numAttrs = 2;
    cudaLaunchKernelEx(&cfg, decode_kernel, (const __nv_bfloat16*)d_in[0], (const __nv_bfloat16*)d_in[1],
                       (const __nv_bfloat16*)d_in[3], (__nv_bfloat16*)d_out, (unsigned long long*)acc, 0u,
                       wq_map, wo_map, v_map);
}
```

```cpp
#include <cuda_runtime.h>
#include <cuda_bf16.h>
#include <cuda.h>
#include <stdint.h>

namespace {

constexpr int SK = 4096, WIN0 = 3072;
constexpr int SLOT = 16384;
constexpr int OFF_BAR  = 6 * SLOT;
constexpr int OFF_QBUF = OFF_BAR + 416;
constexpr int OFF_QS   = OFF_QBUF + 4096;
constexpr int OFF_WST  = OFF_QS + 1024;
constexpr int OB_STRIDE = 576;
constexpr int OFF_OB   = OFF_WST + 192;
constexpr int OFF_HOP  = OFF_OB + 4 * OB_STRIDE;
constexpr int OFF_QRED = OFF_HOP + 2048;
constexpr int OFF_PS   = OFF_QRED;
constexpr int SMEM_BYTES = OFF_QRED + 7 * 1024;
static_assert(SMEM_BYTES <= 115712, "two CTAs must fit on one SM");
constexpr int NTHREADS = 288;
constexpr int SPIN_LIMIT = 1 << 20;

constexpr int T_K0   = 440;
constexpr int T_K    = 662;
constexpr int T_V    = 348;
constexpr int T_V2   = 270;
constexpr int T_GAP  = 30;
constexpr int T_O    = 300;
constexpr int T_LEAD = 1600;
constexpr int MIN_K = 2, MIN_V = 4;

constexpr int ACC_WORDS = 1792 * 2;
__device__ __align__(1024) unsigned long long g_acc[ACC_WORDS];
__device__ float g_side[ACC_WORDS];

__device__ __forceinline__ void mbar_init(uint32_t bar, uint32_t cnt) {
    asm volatile("mbarrier.init.shared::cta.b64 [%0], %1;" ::"r"(bar), "r"(cnt) : "memory");
}
__device__ __forceinline__ void mbar_expect_tx(uint32_t bar, uint32_t bytes) {
    asm volatile("mbarrier.arrive.expect_tx.shared::cta.b64 _, [%0], %1;" ::"r"(bar), "r"(bytes) : "memory");
}
__device__ __forceinline__ void slot_release(uint32_t bar, uint32_t dep, uint32_t zero, int lane) {
    if (lane == 0) asm volatile("mbarrier.arrive.shared::cta.b64 _, [%0];" ::"r"(bar + (dep & zero)) : "memory");
}
__device__ __forceinline__ void mbar_wait_n(uint32_t bar, uint32_t& n) {
    asm volatile("{\n.reg .pred p, q;\n"
                 "WAIT_LOOP:\n"
                 "mbarrier.try_wait.parity.shared::cta.b64 p, [%1], 0;\n"
                 "add.u32 %0, %0, 1;\n"
                 "setp.lt.and.u32 q, %0, %2, !p;\n"
                 "@q bra.uni WAIT_LOOP;\n}"
                 : "+r"(n) : "r"(bar), "n"(SPIN_LIMIT) : "memory");
}
#define mbar_wait(bar) mbar_wait_n(bar, spins)
__device__ __forceinline__ void mbar_wait_fast(uint32_t bar) {
    asm volatile("{\n.reg .pred p;\nWAIT_LOOP:\nmbarrier.try_wait.parity.shared::cta.b64 p, [%0], 0;\n@!p bra.uni WAIT_LOOP;\n}"
                 ::"r"(bar) : "memory");
}
__device__ __forceinline__ uint32_t now_ns() {
    uint32_t t;
    asm volatile("mov.u32 %0, %%globaltimer_lo;" : "=r"(t)::"memory");
    return t;
}
__device__ __forceinline__ void pace(uint32_t due, uint32_t bar) {
    while ((int)(now_ns() - due) < 0) {
        uint32_t ok;
        asm volatile("{\n.reg .pred p;\nmbarrier.test_wait.parity.shared::cta.b64 p, [%1], 0;\nselp.u32 %0, 1, 0, p;\n}"
                     : "=r"(ok) : "r"(bar) : "memory");
        if (ok) break;
    }
}
__device__ __forceinline__ void bulk_g2s(uint32_t dst, const void* src, uint32_t bytes, uint32_t bar) {
    asm volatile("cp.async.bulk.shared::cluster.global.mbarrier::complete_tx::bytes [%0], [%1], %2, [%3];"
                 ::"r"(dst), "l"(src), "r"(bytes), "r"(bar) : "memory");
}
__device__ __forceinline__ void bulk_g2s_mc(uint32_t dst, const void* src, uint32_t bytes, uint32_t bar, uint16_t mask) {
    asm volatile("cp.async.bulk.shared::cluster.global.mbarrier::complete_tx::bytes.multicast::cluster [%0], [%1], %2, [%3], %4;"
                 ::"r"(dst), "l"(src), "r"(bytes), "r"(bar), "h"(mask) : "memory");
}
__device__ __forceinline__ void tma2d(uint32_t dst, const CUtensorMap* tm, int c0, int c1, uint32_t bar) {
    asm volatile("cp.async.bulk.tensor.2d.shared::cluster.global.mbarrier::complete_tx::bytes [%0], [%1, {%3, %4}], [%2];"
                 ::"r"(dst), "l"(tm), "r"(bar), "r"(c0), "r"(c1) : "memory");
}
__device__ __forceinline__ void tma3d(uint32_t dst, const CUtensorMap* tm, int c1, uint32_t bar) {
    asm volatile("cp.async.bulk.tensor.3d.shared::cluster.global.mbarrier::complete_tx::bytes [%0], [%1, {%3, %4, %3}], [%2];"
                 ::"r"(dst), "l"(tm), "r"(bar), "r"(0), "r"(c1) : "memory");
}
__device__ __forceinline__ uint32_t pin(uint32_t v) {
    uint32_t o;
    asm volatile("shfl.sync.bfly.b32 %0, %1, 0, 0x1f, 0xffffffff;" : "=r"(o) : "r"(v));
    return o;
}
template <typename T> __device__ __forceinline__ T* pin_ptr(T* p) {
    const unsigned long long a = (unsigned long long)p;
    return (T*)(((unsigned long long)pin((uint32_t)(a >> 32)) << 32) | pin((uint32_t)a));
}
__device__ __forceinline__ bool elect_one() {
    uint32_t p;
    asm volatile("{\n.reg .pred P;\nelect.sync _|P, 0xffffffff;\nselp.u32 %0, 1, 0, P;\n}" : "=r"(p));
    return p != 0;
}
__device__ __forceinline__ void bar_compute() { asm volatile("bar.sync 1, 256;" ::: "memory"); }
__device__ __forceinline__ void cluster_arrive() { asm volatile("barrier.cluster.arrive.relaxed.aligned;" ::: "memory"); }
__device__ __forceinline__ void cluster_wait() { asm volatile("barrier.cluster.wait.aligned;" ::: "memory"); }
__device__ __forceinline__ void fence_mbar_init() { asm volatile("fence.mbarrier_init.release.cluster;" ::: "memory"); }
__device__ __forceinline__ uint32_t mapa(uint32_t a, uint32_t rank) {
    uint32_t o;
    asm("mapa.shared::cluster.u32 %0, %1, %2;" : "=r"(o) : "r"(a), "r"(rank));
    return o;
}
__device__ __forceinline__ void st_async128(uint32_t a, uint32_t x, uint32_t y, uint32_t z, uint32_t w, uint32_t bar) {
    asm volatile("st.async.shared::cluster.mbarrier::complete_tx::bytes.v4.b32 [%0], {%1,%2,%3,%4}, [%5];"
                 ::"r"(a), "r"(x), "r"(y), "r"(z), "r"(w), "r"(bar) : "memory");
}
__device__ __forceinline__ void st_async64(uint32_t a, uint32_t x, uint32_t y, uint32_t bar) {
    asm volatile("st.async.shared::cluster.mbarrier::complete_tx::bytes.v2.b32 [%0], {%1,%2}, [%3];"
                 ::"r"(a), "r"(x), "r"(y), "r"(bar) : "memory");
}
__device__ __forceinline__ void mma16816(float (&c)[4], const uint4& a, uint32_t b0, uint32_t b1) {
    asm volatile("mma.sync.aligned.m16n8k16.row.col.f32.bf16.bf16.f32 {%0,%1,%2,%3}, {%4,%5,%6,%7}, {%8,%9}, {%0,%1,%2,%3};"
                 : "+f"(c[0]), "+f"(c[1]), "+f"(c[2]), "+f"(c[3])
                 : "r"(a.x), "r"(a.y), "r"(a.z), "r"(a.w), "r"(b0), "r"(b1));
}
__device__ __forceinline__ uint4 lds128(uint32_t a) {
    uint4 v;
    asm volatile("ld.shared.v4.u32 {%0,%1,%2,%3}, [%4];" : "=r"(v.x), "=r"(v.y), "=r"(v.z), "=r"(v.w) : "r"(a) : "memory");
    return v;
}
__device__ __forceinline__ float4 lds128f(uint32_t a) {
    float4 v;
    asm volatile("ld.shared.v4.f32 {%0,%1,%2,%3}, [%4];" : "=f"(v.x), "=f"(v.y), "=f"(v.z), "=f"(v.w) : "r"(a) : "memory");
    return v;
}
__device__ __forceinline__ float2 lds64f(uint32_t a) {
    float2 v;
    asm volatile("ld.shared.v2.f32 {%0,%1}, [%2];" : "=f"(v.x), "=f"(v.y) : "r"(a) : "memory");
    return v;
}
__device__ __forceinline__ uint2 lds64(uint32_t a) {
    uint2 v;
    asm volatile("ld.shared.v2.u32 {%0,%1}, [%2];" : "=r"(v.x), "=r"(v.y) : "r"(a) : "memory");
    return v;
}
__device__ __forceinline__ uint32_t lds32(uint32_t a) {
    uint32_t v;
    asm volatile("ld.shared.u32 %0, [%1];" : "=r"(v) : "r"(a) : "memory");
    return v;
}
__device__ __forceinline__ float lds32f(uint32_t a) { return __uint_as_float(lds32(a)); }
__device__ __forceinline__ void sts128f(uint32_t a, float x, float y, float z, float w) {
    asm volatile("st.shared.v4.f32 [%0], {%1,%2,%3,%4};" ::"r"(a), "f"(x), "f"(y), "f"(z), "f"(w) : "memory");
}
__device__ __forceinline__ void sts32(uint32_t a, uint32_t v) {
    asm volatile("st.shared.u32 [%0], %1;" ::"r"(a), "r"(v) : "memory");
}
__device__ __forceinline__ void sts16(uint32_t a, unsigned short v) {
    asm volatile("st.shared.u16 [%0], %1;" ::"r"(a), "h"(v) : "memory");
}
__device__ __forceinline__ uint4 ldsm4t(uint32_t a) {
    uint4 v;
    asm volatile("ldmatrix.sync.aligned.m8n8.x4.trans.shared.b16 {%0,%1,%2,%3}, [%4];"
                 : "=r"(v.x), "=r"(v.y), "=r"(v.z), "=r"(v.w) : "r"(a) : "memory");
    return v;
}
__device__ __forceinline__ uint32_t pack_bf16(float lo, float hi) {
    uint32_t r;
    asm("cvt.rn.bf16x2.f32 %0, %1, %2;" : "=r"(r) : "f"(hi), "f"(lo));
    return r;
}
__device__ __forceinline__ float round_bf16(float v) { return __uint_as_float(pack_bf16(0.f, v) & 0xFFFF0000u); }
__device__ __forceinline__ float ex2(float x) {
    float y;
    asm("ex2.approx.ftz.f32 %0, %1;" : "=f"(y) : "f"(x));
    return y;
}
__device__ __forceinline__ uint32_t fu(float v) { return __float_as_uint(v); }

__device__ __forceinline__ float acc_value(unsigned long long tot) {
    return fmaf((float)(int)(uint32_t)(tot >> 32), 0x1p-24f, (float)((uint32_t)tot >> 10) * 0x1p-46f);
}
__device__ __noinline__ void finish_with_side(unsigned long long tot, unsigned long long* acc_p, __nv_bfloat16* out_p) {
    if ((tot & 31ull) != 16ull) return;
    __threadfence();
    const float side = atomicExch(&g_side[acc_p - g_acc], 0.0f);
    *out_p = __float2bfloat16(acc_value(tot) + side);
    *acc_p = 0ull;
}
__device__ __noinline__ void accumulate_slow(float sum, unsigned long long* acc_p, __nv_bfloat16* out_p) {
    atomicAdd(&g_side[acc_p - g_acc], sum);
    __threadfence();
    finish_with_side(atomicAdd(acc_p, 33ull) + 33ull, acc_p, out_p);
}

__global__ void __launch_bounds__(NTHREADS, 2)
decode_kernel(const __nv_bfloat16* __restrict__ x, const __nv_bfloat16* __restrict__ kc,
              const __nv_bfloat16* __restrict__ wq, __nv_bfloat16* __restrict__ out,
              unsigned long long* __restrict__ acc, const uint32_t zero,
              const __grid_constant__ CUtensorMap wq_map, const __grid_constant__ CUtensorMap wo_map,
              const __grid_constant__ CUtensorMap v_map) {
    asm volatile("prefetch.global.L2 [%0];" ::"l"((const char*)wq + (blockIdx.x * 224 + min(threadIdx.x, 223u)) * 128));

    extern __shared__ __align__(1024) unsigned char smem[];
    const uint32_t sb = (uint32_t)__cvta_generic_to_shared(smem);
    const int warp = threadIdx.x >> 5, lane = threadIdx.x & 31;
    const int cta = blockIdx.x;
    const int gk = cta >> 4, r = cta & 15, b = r >> 2, s = r & 3;
    const bool proj = r < 14;
    const int c = r - 7 * (r >= 7);
    const uint32_t qfull = sb + OFF_BAR, kfull = qfull + 8, vfull = kfull + 64, ofull = vfull + 128, empty = ofull + 32;
    const uint32_t qbar = empty + 14 * 8, stbar = qbar + 8, obar = qbar + 16, hbar = qbar + 24, done = qbar + 56;
    uint32_t spins = 0;

    if (warp == 0) {
        const bool leader = elect_one();
        if (leader) {
            mbar_init(qfull, 1);
            mbar_expect_tx(qfull, 28672 + 3584);
            tma2d(sb, &wq_map, (cta >> 1) * 64, (cta & 1) * 224, qfull);
            fence_mbar_init();
        }
        uint32_t due = now_ns() + T_K0 - (gk == 7 ? T_LEAD : 0);
        __syncwarp();
        cluster_arrive();
        cluster_wait();
        if (leader) {
            if (proj) bulk_g2s_mc(sb + OFF_OB + r * 256, (const char*)x + r * 256, 256, qfull, (uint16_t)0xFFFF);
            int row = (b * 8 + gk) * SK + WIN0 + s * 256;
            const char* kp = (const char*)kc + (size_t)row * 512;
            uint32_t bar = kfull, dst = sb + 2 * SLOT;
#pragma unroll 1
            for (int i = 0; i < 8; i++) {
                mbar_expect_tx(bar, 16384);
                if (i >= 4) mbar_wait(empty + 8 * (i - 4));
                pace(due, i < MIN_K ? qfull : bar - 8 * MIN_K);
                bulk_g2s(dst, kp, 16384, bar);
                if (i == 1) {
                    asm volatile("prefetch.tensormap [%0];" ::"l"(&v_map) : "memory");
                    asm volatile("prefetch.tensormap [%0];" ::"l"(&wo_map) : "memory");
                }
                due += T_K;
                kp += 16384;
                bar += 8;
                dst = (i == 3) ? sb : dst + SLOT;
            }
#pragma unroll 1
            for (int k = 0; k < 16; k++) {
                mbar_expect_tx(bar, 8192);
                mbar_wait(empty + 8 * (4 + (k >> 1)));
                const int d = k - MIN_V;
                pace(due, vfull + 8 * (d < 0 ? (d >> 1) : d));
                tma3d(dst, &v_map, row, bar);
                due += k < 12 ? T_V : T_V2;
                row += 16;
                bar += 8;
                dst = (k == 3) ? sb : dst + 8192;
            }
            if (proj) {
                due += T_GAP;
                mbar_wait(empty + 8 * 12);
                mbar_wait(empty + 8 * 13);
#pragma unroll 1
                for (int n = 0; n < 4; n++) {
                    mbar_expect_tx(bar, 8192);
                    pace(due, bar - 8);
                    tma2d(sb + n * 8192, &wo_map, c * 64, (2 * gk + (r >= 7)) * 256 + n * 64, bar);
                    due += T_O;
                    bar += 8;
                }
            }
            mbar_wait(done);
            if (spins >= SPIN_LIMIT) __trap();
        }
        return;
    }

    const int w = warp - 1, j = threadIdx.x - 32;
    const int g = lane >> 2, t = lane & 3;

    if (w < 7) {
        cluster_arrive();
        cluster_wait();
        const uint32_t qa = sb + (w * 32 + (lane >> 4) * 8 + (lane & 7)) * 128;
        const uint32_t xa = sb + OFF_OB + (g & 3) * 896 + (cta & 1) * 448 + w * 64 + t * 4;
        mbar_wait(qfull);
        const uint32_t x0 = lds32(xa), x1 = lds32(xa + 16), x2 = lds32(xa + 32), x3 = lds32(xa + 48);
        float cq[4][4];
#pragma unroll
        for (int m = 0; m < 4; m++) {
            const uint32_t a = qa + (((2 * m + ((lane >> 3) & 1)) ^ (lane & 7)) << 4);
            const uint4 f0 = ldsm4t(a), f1 = ldsm4t(a + 2048);
            cq[m][0] = cq[m][1] = cq[m][2] = cq[m][3] = 0.f;
            mma16816(cq[m], f0, x0, x1);
            mma16816(cq[m], f1, x2, x3);
        }
        slot_release(empty + 8 * (w >> 2), fu(cq[0][0]) ^ fu(cq[1][0]) ^ fu(cq[2][0]) ^ fu(cq[3][0]), zero, lane);
        const int hf = t >> 1;
        const uint32_t qr = sb + OFF_QRED + w * 1024 + (t & 1) * 512 + hf * 128 + g * 16;
        sts128f(qr, hf ? cq[0][2] : cq[0][0], hf ? cq[1][2] : cq[1][0], hf ? cq[2][2] : cq[2][0], hf ? cq[3][2] : cq[3][0]);
        sts128f(qr + 256, hf ? cq[0][3] : cq[0][1], hf ? cq[1][3] : cq[1][1], hf ? cq[2][3] : cq[2][1], hf ? cq[3][3] : cq[3][1]);
    } else {
        if (lane == 0) {
#pragma unroll
            for (int i = 0; i < 28; i++) mbar_init(kfull + 8 * i, 1);
#pragma unroll
            for (int i = 0; i < 14; i++) mbar_init(empty + 8 * i, i == 1 ? 3 : (i < 10 ? 4 : 8));
#pragma unroll
            for (int i = 0; i < 7; i++) mbar_init(qbar + 8 * i, 1);
            mbar_init(done, 8);
            mbar_expect_tx(qbar, 4096);
            mbar_expect_tx(stbar, 64);
            mbar_expect_tx(obar, 2048);
#pragma unroll
            for (int i = 0; i < 4; i++) mbar_expect_tx(hbar + 8 * i, 512);
            fence_mbar_init();
        }
        __syncwarp();
        cluster_arrive();
        cluster_wait();
    }
    bar_compute();
    {
        const int pk = j >> 2;
        const uint32_t ra = sb + OFF_QRED + pk * 16;
        float4 a = lds128f(ra);
#pragma unroll
        for (int ww = 1; ww < 7; ww++) {
            const float4 v = lds128f(ra + ww * 1024);
            a.x += v.x; a.y += v.y; a.z += v.z; a.w += v.w;
        }
        const uint32_t dst = (pk >> 4) * 4 + (j & 3);
        st_async128(mapa(sb + OFF_QBUF + (r & 1) * 2048 + (r >> 1) * 256 + (pk & 15) * 16, dst),
                    fu(a.x), fu(a.y), fu(a.z), fu(a.w), mapa(qbar, dst));
        mbar_wait(qbar);
        const uint32_t qb = sb + OFF_QBUF + (j >> 5) * 256 + (j & 7) * 32 + ((j >> 3) & 3) * 4;
        const float q0 = lds32f(qb) + lds32f(qb + 2048), q1 = lds32f(qb + 16) + lds32f(qb + 2064);
        sts32(sb + OFF_QS + ((j >> 5) & 3) * 256 + (j & 1) * 128 + (j >> 7) * 64 + ((j >> 2) & 3) * 16 + ((j >> 4) & 1) * 8 + ((j >> 1) & 1) * 4,
              pack_bf16(q0, q1));
    }
    bar_compute();

    float s0 = 0.f, s1 = 0.f;
    {
        uint2 qf[8];
        const uint32_t qa = sb + OFF_QS + (g >> 2) * 128 + (g & 1) * 64 + t * 16;
        const uint32_t qx = ((g >> 1) & 1) * 8;
#pragma unroll
        for (int i = 0; i < 8; i++) qf[i] = lds64(qa + (i >> 1) * 256 + (((i & 1) * 8) ^ qx));
        const uint32_t kx = (g & 1) * 64;
        const uint32_t krow = sb + ((w & 3) * 8 + g) * 512 + t * 16;
        const int src = (lane & 28) + (g & 1);
#pragma unroll 1
        for (int k = 0; k < 4; k++) {
            const int ch = 2 * k + (w >> 2);
            const uint32_t ka = krow + (ch >= 4 ? ch - 4 : ch + 2) * SLOT;
            mbar_wait(kfull + 8 * ch);
            float a0[4] = {0.f, 0.f, 0.f, 0.f}, a1[4] = {0.f, 0.f, 0.f, 0.f};
#pragma unroll
            for (int i = 0; i < 8; i += 2) {
                const uint4 r0 = lds128(ka + ((i * 64) ^ kx)), r1 = lds128(ka + (((i + 1) * 64) ^ kx));
                mma16816(a0, r0, qf[i].x, qf[i].y);
                mma16816(a1, r1, qf[i + 1].x, qf[i + 1].y);
            }
            const float e0 = __shfl_sync(0xffffffffu, a0[0] + a1[0], src) + __shfl_sync(0xffffffffu, a0[2] + a1[2], src + 2);
            const float e1 = __shfl_sync(0xffffffffu, a0[1] + a1[1], src) + __shfl_sync(0xffffffffu, a0[3] + a1[3], src + 2);
            slot_release(empty + 8 * (2 + ch), fu(e0), zero, lane);
            if (t == k) { s0 = e0; s1 = e1; }
        }
    }
    float Mown;
    {
        const float kscale = 0.0625f * 1.4426950408889634f;
        s0 = round_bf16(s0) * kscale;
        s1 = round_bf16(s1) * kscale;
        float m0 = s0, m1 = s1;
#pragma unroll
        for (int o = 16; o > 0; o >>= 1) {
            m0 = fmaxf(m0, __shfl_xor_sync(0xffffffffu, m0, o));
            m1 = fmaxf(m1, __shfl_xor_sync(0xffffffffu, m1, o));
        }
        if (lane < 2) sts32(sb + OFF_WST + (w * 2 + lane) * 4, fu(lane ? m1 : m0));
        bar_compute();
        const float4 u0 = lds128f(sb + OFF_WST), u1 = lds128f(sb + OFF_WST + 16), u2 = lds128f(sb + OFF_WST + 32), u3 = lds128f(sb + OFF_WST + 48);
        const float M0 = fmaxf(fmaxf(fmaxf(u0.x, u0.z), fmaxf(u1.x, u1.z)), fmaxf(fmaxf(u2.x, u2.z), fmaxf(u3.x, u3.z)));
        const float M1 = fmaxf(fmaxf(fmaxf(u0.y, u0.w), fmaxf(u1.y, u1.w)), fmaxf(fmaxf(u2.y, u2.w), fmaxf(u3.y, u3.w)));
        Mown = (t & 1) ? M1 : M0;
        const uint32_t p = pack_bf16(ex2(s0 - M0), ex2(s1 - M1));
        const uint32_t pa = sb + OFF_PS + (4 * t + (w >> 1)) * 64 + (g >> 1) * 8 + (w & 1) * 4 + (g & 1) * 2;
        sts16(pa, (unsigned short)(p & 0xFFFFu));
        sts16(pa + 32, (unsigned short)(p >> 16));
        float l0 = __uint_as_float(p << 16), l1 = __uint_as_float(p & 0xFFFF0000u);
#pragma unroll
        for (int o = 16; o > 0; o >>= 1) {
            l0 += __shfl_xor_sync(0xffffffffu, l0, o);
            l1 += __shfl_xor_sync(0xffffffffu, l1, o);
        }
        if (lane < 2) sts32(sb + OFF_WST + 64 + (w * 2 + lane) * 4, fu(lane ? l1 : l0));
        bar_compute();
        if (j < 4) {
            const float4 v0 = lds128f(sb + OFF_WST + 64), v1 = lds128f(sb + OFF_WST + 80), v2 = lds128f(sb + OFF_WST + 96), v3 = lds128f(sb + OFF_WST + 112);
            const float L0 = ((v0.x + v0.z) + (v1.x + v1.z)) + ((v2.x + v2.z) + (v3.x + v3.z));
            const float L1 = ((v0.y + v0.w) + (v1.y + v1.w)) + ((v2.y + v2.w) + (v3.y + v3.w));
            st_async128(mapa(sb + OFF_WST + 128 + s * 16, b * 4 + j), fu(M0), fu(L0), fu(M1), fu(L1), mapa(stbar, b * 4 + j));
        }
    }

    const uint32_t h1_dst = pin(mapa(sb + OFF_HOP + r * 128 + (t >> 1) * 64 + g * 8, (t & 1) * 8 + w));
    const uint32_t h1_bar = pin(mapa(hbar + 8 * b, (t & 1) * 8 + w));
    const uint32_t h2_grp = (w >> 2) * 4 + (lane >> 3);
    const uint32_t h2_rank = h2_grp < 7 ? (r >> 3) * 7 + h2_grp : 14 + (r >> 3);
    const uint32_t h2_dst = pin(mapa(sb + OFF_OB + (w & 3) * OB_STRIDE + (r & 7) * 64 + (lane & 3) * 16 + ((lane >> 2) & 1) * 8, h2_rank));
    const uint32_t h2_bar = pin(mapa(obar, h2_rank));
    const uint32_t h2_src = pin(sb + OFF_HOP + (w & 3) * 512 + (lane & 7) * 16);
    const uint32_t h2_wait = pin(hbar + 8 * (w & 3));
    const uint32_t bars = pin(obar);
    const uint32_t wo_src = pin(sb + (((lane >> 3) & 1) * 16 + (lane >> 4) * 8 + (lane & 7)) * 128 + ((w ^ (lane & 7)) << 4));
    const uint32_t ob_src = pin(sb + OFF_OB + (g & 3) * OB_STRIDE + (g >> 2) * 64 + t * 16);
    unsigned long long* acc_p = pin_ptr(acc + (c * 16 + (j >> 4)) * 32 + (j & 15));
    __nv_bfloat16* out_p = pin_ptr(out + (g & 3) * 448 + c * 64 + w * 8 + 2 * t + (g >> 2));
    const uint32_t k_one = pin(zero + 1u);
    const bool t_hi = pin(t >> 1) != 0, g_hi = pin(g >> 2) != 0, proj_on = pin(proj ? 1u : 0u) != 0;

    float acc0[4] = {0.f, 0.f, 0.f, 0.f}, acc1[4] = {0.f, 0.f, 0.f, 0.f};
    float wgt;
    {
        const uint32_t va0 = pin(sb + (w >> 1) * 2048 + ((lane >> 4) * 8 + (lane & 7)) * 128 + ((((w & 1) * 4 + ((lane >> 3) & 1)) ^ (lane & 7)) << 4));
        const uint32_t va1 = pin(va0 ^ 32);
        const uint32_t pa = pin(sb + OFF_PS + ((g >> 1) & 1) * 32 + t * 8);
        const uint32_t vb = bars - (obar - vfull);
#pragma unroll 1
        for (int k = 0; k < 8; k += 2) {
            const uint32_t so = (k < 4 ? k + 8 : k - 4) * 8192;
            const uint2 p0 = lds64(pa + k * 64), p1 = lds64(pa + k * 64 + 64);
            mbar_wait(vb + 8 * k);
            const uint4 f0 = ldsm4t(va0 + so), f1 = ldsm4t(va1 + so);
            mma16816(acc0, f0, p0.x, p0.y);
            mma16816(acc1, f1, p0.x, p0.y);
            mbar_wait(vb + 8 * k + 8);
            const uint4 f2 = ldsm4t(va0 + so + 8192), f3 = ldsm4t(va1 + so + 8192);
            mma16816(acc0, f2, p1.x, p1.y);
            mma16816(acc1, f3, p1.x, p1.y);
            slot_release(empty + 8 * (10 + (k >> 1)), fu(acc0[0]) ^ fu(acc1[0]), zero, lane);
        }
        uint2 pw[8];
#pragma unroll
        for (int k = 8; k < 16; k++) pw[k - 8] = lds64(pa + k * 64);
        {
            mbar_wait(stbar);
            const uint32_t sa = sb + OFF_WST + 128 + (t & 1) * 8;
            const float2 z0 = lds64f(sa), z1 = lds64f(sa + 16), z2 = lds64f(sa + 32), z3 = lds64f(sa + 48);
            const float mx = fmaxf(fmaxf(z0.x, z1.x), fmaxf(z2.x, z3.x));
            const float W = (ex2(z0.x - mx) * z0.y + ex2(z1.x - mx) * z1.y) + (ex2(z2.x - mx) * z2.y + ex2(z3.x - mx) * z3.y);
            wgt = __uint_as_float(pin(fu(__fdividef(ex2(Mown - mx), W))));
        }
        uint4 f0, f1;
#pragma unroll
        for (int k = 8; k < 16; k++) {
            mbar_wait_fast(vb + 8 * k);
            const uint4 n0 = ldsm4t(va0 + (k - 4) * 8192), n1 = ldsm4t(va1 + (k - 4) * 8192);
            if (k > 8) {
                mma16816(acc0, f0, pw[k - 9].x, pw[k - 9].y);
                mma16816(acc1, f1, pw[k - 9].x, pw[k - 9].y);
            }
            f0 = n0; f1 = n1;
        }
        mma16816(acc0, f0, pw[7].x, pw[7].y);
        mma16816(acc1, f1, pw[7].x, pw[7].y);
    }
    st_async64(h1_dst, fu((t_hi ? acc1[0] : acc0[0]) * wgt), fu((t_hi ? acc1[2] : acc0[2]) * wgt), h1_bar);
    {
        mbar_wait_fast(h2_wait);
        const float4 v0 = lds128f(h2_src), v1 = lds128f(h2_src + 128), v2 = lds128f(h2_src + 256), v3 = lds128f(h2_src + 384);
        st_async64(h2_dst, pack_bf16((v0.x + v1.x) + (v2.x + v3.x), (v0.z + v1.z) + (v2.z + v3.z)),
                   pack_bf16((v0.y + v1.y) + (v2.y + v3.y), (v0.w + v1.w) + (v2.w + v3.w)), h2_bar);
    }
    if (!proj_on) {
        mbar_wait_fast(bars);
        slot_release(bars + (done - obar), 0u, 0u, lane);
        return;
    }
    float sum;
    {
        const uint32_t ob = bars - (obar - ofull);
        float x0[4] = {0.f, 0.f, 0.f, 0.f}, x1[4] = {0.f, 0.f, 0.f, 0.f}, y0[4] = {0.f, 0.f, 0.f, 0.f}, y1[4] = {0.f, 0.f, 0.f, 0.f};
        uint4 bp[4], bq[4], oa[4];
#pragma unroll
        for (int n = 0; n < 3; n++) {
            mbar_wait_fast(ob + 8 * n);
            bp[n] = ldsm4t(wo_src + n * 8192);
            bq[n] = ldsm4t(wo_src + n * 8192 + 4096);
        }
        mbar_wait_fast(bars);
#pragma unroll
        for (int n = 0; n < 4; n++) oa[n] = lds128(ob_src + n * 128);
#pragma unroll
        for (int n = 0; n < 4; n++) {
            if (n == 3) {
                mbar_wait_fast(ob + 24);
                bp[3] = ldsm4t(wo_src + 3 * 8192);
                bq[3] = ldsm4t(wo_src + 3 * 8192 + 4096);
            }
            mma16816(x0, oa[n], bp[n].x, bp[n].y);
            mma16816(y0, oa[n], bp[n].z, bp[n].w);
            mma16816(x1, oa[n], bq[n].x, bq[n].y);
            mma16816(y1, oa[n], bq[n].z, bq[n].w);
        }
        float keep = x0[0] + y0[2], send = x0[1] + y0[3];
        if (g_hi) { send = x1[0] + y1[2]; keep = x1[1] + y1[3]; }
        sum = keep + __shfl_xor_sync(0xffffffffu, send, 16);
    }
    const uint32_t bits = fu(sum);
    const uint32_t sh = 129u - ((bits >> 23) & 0xFFu);
    const uint32_t smant = (((bits << 3) & 0x3FFFFF8u) | 0x4000000u) ^ (uint32_t)((int)bits >> 31);
    long long fx;
    asm("shr.s64 %0, %1, %2;" : "=l"(fx) : "l"((long long)((unsigned long long)smant << 32)), "r"(sh));
    const unsigned long long inc = ((unsigned long long)fx & 0xFFFFFFFF00000000ull) | (((uint32_t)fx & ~0x3FFu) | k_one);
    const bool fast = __any_sync(0xffffffffu, fabsf(sum) >= 0x1p-22f) && fabsf(sum) < 8.0f;
    unsigned long long tot = 0ull;
    asm volatile("{\n.reg .pred p;\nsetp.ne.u32 p, %3, 0;\n@p atom.relaxed.gpu.global.add.u64 %0, [%1], %2;\n}"
                 : "+l"(tot) : "l"(acc_p), "l"(inc), "r"((uint32_t)fast) : "memory");
    slot_release(bars + (done - obar), 0u, 0u, lane);
    if (!fast) { accumulate_slow(sum, acc_p, out_p); return; }
    tot += inc;
    const uint32_t cnt = (uint32_t)tot & 0x3FFu;
    asm volatile("{\n.reg .pred p;\nsetp.eq.u32 p, %3, 16;\n@p st.global.u16 [%0], %1;\n@p st.global.u64 [%2], 0;\n}"
                 ::"l"(out_p), "h"(__bfloat16_as_ushort(__float2bfloat16(acc_value(tot)))), "l"(acc_p), "r"(cnt) : "memory");
    if (cnt > 16u) finish_with_side(tot, acc_p, out_p);
}

typedef CUresult (*EncodeFn)(CUtensorMap*, CUtensorMapDataType, cuuint32_t, void*, const cuuint64_t*, const cuuint64_t*,
                             const cuuint32_t*, const cuuint32_t*, CUtensorMapInterleave, CUtensorMapSwizzle,
                             CUtensorMapL2promotion, CUtensorMapFloatOOBfill);

}

extern "C" void kernel_launch(void* const* d_in, const int* in_sizes, int n_in, void* d_out, int out_size) {
    (void)in_sizes; (void)n_in; (void)out_size;
    static EncodeFn encode = nullptr;
    static void* acc = nullptr;
    if (!encode) {
        cudaDriverEntryPointQueryResult qr;
        cudaGetDriverEntryPoint("cuTensorMapEncodeTiled", (void**)&encode, cudaEnableDefault, &qr);
        cudaGetSymbolAddress(&acc, g_acc);
        cudaFuncSetAttribute(decode_kernel, cudaFuncAttributeMaxDynamicSharedMemorySize, SMEM_BYTES);
        cudaFuncSetAttribute(decode_kernel, cudaFuncAttributeNonPortableClusterSizeAllowed, 1);
    }
    const cuuint32_t estr[3] = {1, 1, 1};
    CUtensorMap wq_map, wo_map, v_map;
    {
        const cuuint64_t dim[2] = {4096, 448}, str[1] = {8192};
        const cuuint32_t box[2] = {64, 224};
        encode(&wq_map, CU_TENSOR_MAP_DATA_TYPE_BFLOAT16, 2, d_in[3], dim, str, box, estr, CU_TENSOR_MAP_INTERLEAVE_NONE,
               CU_TENSOR_MAP_SWIZZLE_128B, CU_TENSOR_MAP_L2_PROMOTION_NONE, CU_TENSOR_MAP_FLOAT_OOB_FILL_NONE);
    }
    {
        const cuuint64_t dim[2] = {448, 4096}, str[1] = {896};
        const cuuint32_t box[2] = {64, 64};
        encode(&wo_map, CU_TENSOR_MAP_DATA_TYPE_BFLOAT16, 2, d_in[4], dim, str, box, estr, CU_TENSOR_MAP_INTERLEAVE_NONE,
               CU_TENSOR_MAP_SWIZZLE_128B, CU_TENSOR_MAP_L2_PROMOTION_NONE, CU_TENSOR_MAP_FLOAT_OOB_FILL_NONE);
    }
    {
        const cuuint64_t dim[3] = {64, 4ull * 8 * SK, 4}, str[2] = {512, 128};
        const cuuint32_t box[3] = {64, 16, 4};
        encode(&v_map, CU_TENSOR_MAP_DATA_TYPE_BFLOAT16, 3, d_in[2], dim, str, box, estr, CU_TENSOR_MAP_INTERLEAVE_NONE,
               CU_TENSOR_MAP_SWIZZLE_128B, CU_TENSOR_MAP_L2_PROMOTION_NONE, CU_TENSOR_MAP_FLOAT_OOB_FILL_NONE);
    }
    cudaLaunchConfig_t cfg = {};
    cfg.gridDim = dim3(128);
    cfg.blockDim = dim3(NTHREADS);
    cfg.dynamicSmemBytes = SMEM_BYTES;
    cfg.stream = cudaStreamPerThread;
    cudaLaunchAttribute attr[2];
    attr[0].id = cudaLaunchAttributeClusterDimension;
    attr[0].val.clusterDim.x = 16; attr[0].val.clusterDim.y = 1; attr[0].val.clusterDim.z = 1;
    attr[1].id = cudaLaunchAttributeClusterSchedulingPolicyPreference;
    attr[1].val.clusterSchedulingPolicyPreference = cudaClusterSchedulingPolicyLoadBalancing;
    cfg.attrs = attr;
    cfg.numAttrs = 2;
    cudaLaunchKernelEx(&cfg, decode_kernel, (const __nv_bfloat16*)d_in[0], (const __nv_bfloat16*)d_in[1],
                       (const __nv_bfloat16*)d_in[3], (__nv_bfloat16*)d_out, (unsigned long long*)acc, 0u,
                       wq_map, wo_map, v_map);
}
```

```cpp
#include <cuda_runtime.h>
#include <cuda_bf16.h>
#include <cuda.h>
#include <stdint.h>

namespace {

constexpr int SK = 4096, WIN0 = 3072;
constexpr int SLOT = 16384;
constexpr int OFF_BAR  = 6 * SLOT;
constexpr int OFF_QBUF = OFF_BAR + 416;
constexpr int OFF_QS   = OFF_QBUF + 4096;
constexpr int OFF_WST  = OFF_QS + 1024;
constexpr int OB_STRIDE = 576;
constexpr int OFF_OB   = OFF_WST + 192;
constexpr int OFF_HOP  = OFF_OB + 4 * OB_STRIDE;
constexpr int OFF_QRED = OFF_HOP + 2048;
constexpr int OFF_PS   = OFF_QRED;
constexpr int SMEM_BYTES = OFF_QRED + 7 * 1024;
static_assert(SMEM_BYTES <= 115712, "two CTAs must fit on one SM");
constexpr int NTHREADS = 288;
constexpr int SPIN_LIMIT = 1 << 20;

#define TK0 410
#define TDV 348
#define TGAP 30
#define TDO 300
#define T7 1600
#define WLK 2
#define WLV 4
#define TDK 662
#define TDV2 270
#define WG 32
#define RM 1
#define ROT(c, gk) (RM == 0 ? 0 : (RM == 1 ? (c) : (RM == 2 ? (gk) : (c) + (gk))))
#define WLO 1

constexpr int ACC_WORDS = 1792 * 2;
__device__ __align__(1024) unsigned long long g_acc[ACC_WORDS];
__device__ float g_side[ACC_WORDS];

#define GT_AT(n)
#define GT_END()

__device__ __forceinline__ void mbar_init(uint32_t bar, uint32_t cnt) {
    asm volatile("mbarrier.init.shared::cta.b64 [%0], %1;" ::"r"(bar), "r"(cnt) : "memory");
}
__device__ __forceinline__ void mbar_expect_tx(uint32_t bar, uint32_t bytes) {
    asm volatile("mbarrier.arrive.expect_tx.shared::cta.b64 _, [%0], %1;" ::"r"(bar), "r"(bytes) : "memory");
}
__device__ __forceinline__ void slot_release(uint32_t bar, uint32_t dep, uint32_t zero, int lane) {
    if (lane == 0) asm volatile("mbarrier.arrive.shared::cta.b64 _, [%0];" ::"r"(bar + (dep & zero)) : "memory");
}
__device__ __forceinline__ void mbar_wait_n(uint32_t bar, uint32_t& n) {
    asm volatile("{\n.reg .pred p, q;\n"
                 "WAIT_LOOP:\n"
                 "mbarrier.try_wait.parity.shared::cta.b64 p, [%1], 0;\n"
                 "add.u32 %0, %0, 1;\n"
                 "setp.lt.and.u32 q, %0, %2, !p;\n"
                 "@q bra.uni WAIT_LOOP;\n}"
                 : "+r"(n) : "r"(bar), "n"(SPIN_LIMIT) : "memory");
}
#define mbar_wait(bar) mbar_wait_n(bar, spins)
__device__ __forceinline__ void mbar_wait_fast(uint32_t bar) {
    asm volatile("{\n.reg .pred p;\nWAIT_LOOP:\nmbarrier.try_wait.parity.shared::cta.b64 p, [%0], 0;\n@!p bra.uni WAIT_LOOP;\n}"
                 ::"r"(bar) : "memory");
}
__device__ __forceinline__ uint32_t now_ns() {
    uint32_t t;
    asm volatile("mov.u32 %0, %%globaltimer_lo;" : "=r"(t)::"memory");
    return t;
}
__device__ __forceinline__ void pace(uint32_t due, uint32_t bar) {
    while ((int)(now_ns() - due) < 0) {
        uint32_t ok;
        asm volatile("{\n.reg .pred p;\nmbarrier.test_wait.parity.shared::cta.b64 p, [%1], 0;\nselp.u32 %0, 1, 0, p;\n}"
                     : "=r"(ok) : "r"(bar) : "memory");
        if (ok) break;
    }
}
__device__ __forceinline__ void bulk_g2s(uint32_t dst, const void* src, uint32_t bytes, uint32_t bar) {
    asm volatile("cp.async.bulk.shared::cluster.global.mbarrier::complete_tx::bytes [%0], [%1], %2, [%3];"
                 ::"r"(dst), "l"(src), "r"(bytes), "r"(bar) : "memory");
}
__device__ __forceinline__ void bulk_g2s_mc(uint32_t dst, const void* src, uint32_t bytes, uint32_t bar, uint16_t mask) {
    asm volatile("cp.async.bulk.shared::cluster.global.mbarrier::complete_tx::bytes.multicast::cluster [%0], [%1], %2, [%3], %4;"
                 ::"r"(dst), "l"(src), "r"(bytes), "r"(bar), "h"(mask) : "memory");
}
__device__ __forceinline__ void tma2d(uint32_t dst, const CUtensorMap* tm, int c0, int c1, uint32_t bar) {
    asm volatile("cp.async.bulk.tensor.2d.shared::cluster.global.mbarrier::complete_tx::bytes [%0], [%1, {%3, %4}], [%2];"
                 ::"r"(dst), "l"(tm), "r"(bar), "r"(c0), "r"(c1) : "memory");
}
__device__ __forceinline__ void tma3d(uint32_t dst, const CUtensorMap* tm, int c1, uint32_t bar) {
    asm volatile("cp.async.bulk.tensor.3d.shared::cluster.global.mbarrier::complete_tx::bytes [%0], [%1, {%3, %4, %3}], [%2];"
                 ::"r"(dst), "l"(tm), "r"(bar), "r"(0), "r"(c1) : "memory");
}
__device__ __forceinline__ void tma4d(uint32_t dst, const CUtensorMap* tm, int c0, int c2, int c3, uint32_t bar) {
    asm volatile("cp.async.bulk.tensor.4d.shared::cluster.global.mbarrier::complete_tx::bytes [%0], [%1, {%3, %4, %5, %6}], [%2];"
                 ::"r"(dst), "l"(tm), "r"(bar), "r"(c0), "r"(0), "r"(c2), "r"(c3) : "memory");
}
__device__ __forceinline__ uint32_t pin(uint32_t v) {
    uint32_t o;
    asm volatile("shfl.sync.bfly.b32 %0, %1, 0, 0x1f, 0xffffffff;" : "=r"(o) : "r"(v));
    return o;
}
template <typename T> __device__ __forceinline__ T* pin_ptr(T* p) {
    const unsigned long long a = (unsigned long long)p;
    return (T*)(((unsigned long long)pin((uint32_t)(a >> 32)) << 32) | pin((uint32_t)a));
}
__device__ __forceinline__ bool elect_one() {
    uint32_t p;
    asm volatile("{\n.reg .pred P;\nelect.sync _|P, 0xffffffff;\nselp.u32 %0, 1, 0, P;\n}" : "=r"(p));
    return p != 0;
}
__device__ __forceinline__ void bar_compute() { asm volatile("bar.sync 1, 256;" ::: "memory"); }
__device__ __forceinline__ void cluster_arrive() { asm volatile("barrier.cluster.arrive.relaxed.aligned;" ::: "memory"); }
__device__ __forceinline__ void cluster_wait() { asm volatile("barrier.cluster.wait.aligned;" ::: "memory"); }
__device__ __forceinline__ void fence_mbar_init() { asm volatile("fence.mbarrier_init.release.cluster;" ::: "memory"); }
__device__ __forceinline__ uint32_t mapa(uint32_t a, uint32_t rank) {
    uint32_t o;
    asm("mapa.shared::cluster.u32 %0, %1, %2;" : "=r"(o) : "r"(a), "r"(rank));
    return o;
}
__device__ __forceinline__ void st_async128(uint32_t a, uint32_t x, uint32_t y, uint32_t z, uint32_t w, uint32_t bar) {
    asm volatile("st.async.shared::cluster.mbarrier::complete_tx::bytes.v4.b32 [%0], {%1,%2,%3,%4}, [%5];"
                 ::"r"(a), "r"(x), "r"(y), "r"(z), "r"(w), "r"(bar) : "memory");
}
__device__ __forceinline__ void st_async64(uint32_t a, uint32_t x, uint32_t y, uint32_t bar) {
    asm volatile("st.async.shared::cluster.mbarrier::complete_tx::bytes.v2.b32 [%0], {%1,%2}, [%3];"
                 ::"r"(a), "r"(x), "r"(y), "r"(bar) : "memory");
}
__device__ __forceinline__ void mma16816(float (&c)[4], const uint4& a, uint32_t b0, uint32_t b1) {
    asm volatile("mma.sync.aligned.m16n8k16.row.col.f32.bf16.bf16.f32 {%0,%1,%2,%3}, {%4,%5,%6,%7}, {%8,%9}, {%0,%1,%2,%3};"
                 : "+f"(c[0]), "+f"(c[1]), "+f"(c[2]), "+f"(c[3])
                 : "r"(a.x), "r"(a.y), "r"(a.z), "r"(a.w), "r"(b0), "r"(b1));
}
__device__ __forceinline__ uint4 lds128(uint32_t a) {
    uint4 v;
    asm volatile("ld.shared.v4.u32 {%0,%1,%2,%3}, [%4];" : "=r"(v.x), "=r"(v.y), "=r"(v.z), "=r"(v.w) : "r"(a) : "memory");
    return v;
}
__device__ __forceinline__ float4 lds128f(uint32_t a) {
    float4 v;
    asm volatile("ld.shared.v4.f32 {%0,%1,%2,%3}, [%4];" : "=f"(v.x), "=f"(v.y), "=f"(v.z), "=f"(v.w) : "r"(a) : "memory");
    return v;
}
__device__ __forceinline__ float2 lds64f(uint32_t a) {
    float2 v;
    asm volatile("ld.shared.v2.f32 {%0,%1}, [%2];" : "=f"(v.x), "=f"(v.y) : "r"(a) : "memory");
    return v;
}
__device__ __forceinline__ uint2 lds64(uint32_t a) {
    uint2 v;
    asm volatile("ld.shared.v2.u32 {%0,%1}, [%2];" : "=r"(v.x), "=r"(v.y) : "r"(a) : "memory");
    return v;
}
__device__ __forceinline__ uint32_t lds32(uint32_t a) {
    uint32_t v;
    asm volatile("ld.shared.u32 %0, [%1];" : "=r"(v) : "r"(a) : "memory");
    return v;
}
__device__ __forceinline__ float lds32f(uint32_t a) { return __uint_as_float(lds32(a)); }
__device__ __forceinline__ void sts128f(uint32_t a, float x, float y, float z, float w) {
    asm volatile("st.shared.v4.f32 [%0], {%1,%2,%3,%4};" ::"r"(a), "f"(x), "f"(y), "f"(z), "f"(w) : "memory");
}
__device__ __forceinline__ void sts32(uint32_t a, uint32_t v) {
    asm volatile("st.shared.u32 [%0], %1;" ::"r"(a), "r"(v) : "memory");
}
__device__ __forceinline__ void sts16(uint32_t a, unsigned short v) {
    asm volatile("st.shared.u16 [%0], %1;" ::"r"(a), "h"(v) : "memory");
}
__device__ __forceinline__ uint4 ldsm4t(uint32_t a) {
    uint4 v;
    asm volatile("ldmatrix.sync.aligned.m8n8.x4.trans.shared.b16 {%0,%1,%2,%3}, [%4];"
                 : "=r"(v.x), "=r"(v.y), "=r"(v.z), "=r"(v.w) : "r"(a) : "memory");
    return v;
}
__device__ __forceinline__ uint32_t pack_bf16(float lo, float hi) {
    uint32_t r;
    asm("cvt.rn.bf16x2.f32 %0, %1, %2;" : "=r"(r) : "f"(hi), "f"(lo));
    return r;
}
__device__ __forceinline__ float round_bf16(float v) { return __uint_as_float(pack_bf16(0.f, v) & 0xFFFF0000u); }
__device__ __forceinline__ float ex2(float x) {
    float y;
    asm("ex2.approx.ftz.f32 %0, %1;" : "=f"(y) : "f"(x));
    return y;
}
__device__ __forceinline__ uint32_t fu(float v) { return __float_as_uint(v); }

__device__ __forceinline__ float acc_value(unsigned long long tot) {
    return fmaf((float)(int)(uint32_t)(tot >> 32), 0x1p-24f, (float)((uint32_t)tot >> 10) * 0x1p-46f);
}
__device__ __noinline__ void finish_with_side(unsigned long long tot, unsigned long long* acc_p, __nv_bfloat16* out_p) {
    if ((tot & 31ull) != 16ull) return;
    __threadfence();
    const float side = atomicExch(&g_side[acc_p - g_acc], 0.0f);
    *out_p = __float2bfloat16(acc_value(tot) + side);
    *acc_p = 0ull;
}
__device__ __noinline__ void accumulate_slow(float sum, unsigned long long* acc_p, __nv_bfloat16* out_p) {
    atomicAdd(&g_side[acc_p - g_acc], sum);
    __threadfence();
    finish_with_side(atomicAdd(acc_p, 33ull) + 33ull, acc_p, out_p);
}

__global__ void __launch_bounds__(NTHREADS, 2)
decode_kernel(const __nv_bfloat16* __restrict__ x, const __nv_bfloat16* __restrict__ kc,
              const __nv_bfloat16* __restrict__ wq, __nv_bfloat16* __restrict__ out,
              unsigned long long* __restrict__ acc, const uint32_t zero,
              const __grid_constant__ CUtensorMap wq_map, const __grid_constant__ CUtensorMap wo_map,
              const __grid_constant__ CUtensorMap v_map) {
    asm volatile("prefetch.global.L2 [%0];" ::"l"((const char*)wq + (blockIdx.x * 224 + min(threadIdx.x, 223u)) * 128));

    extern __shared__ __align__(1024) unsigned char smem[];
    const uint32_t sb = (uint32_t)__cvta_generic_to_shared(smem);
    const int warp = threadIdx.x >> 5, lane = threadIdx.x & 31;
    const int cta = blockIdx.x;
    const int gk = cta >> 4, r = cta & 15, b = r >> 2, s = r & 3;
    const bool proj = r < 14;
    const int c = r - 7 * (r >= 7);
    const uint32_t qfull = sb + OFF_BAR, kfull = qfull + 8, vfull = kfull + 64, ofull = vfull + 128, empty = ofull + 32;
    const uint32_t qbar = empty + 14 * 8, stbar = qbar + 8, obar = qbar + 16, hbar = qbar + 24, done = qbar + 56;
    uint32_t spins = 0;

    if (warp == 0) {
        const bool leader = elect_one();
        if (leader) {
            mbar_init(qfull, 1);
            mbar_expect_tx(qfull, 28672 + 3584);
            tma2d(sb, &wq_map, (cta >> 1) * 64, (cta & 1) * 224, qfull);
            fence_mbar_init();
        }
        uint32_t due = now_ns() + TK0 - (gk == 7 ? T7 : 0);
        __syncwarp();
        cluster_arrive();
        cluster_wait();
        if (leader) {
            if (proj) bulk_g2s_mc(sb + OFF_OB + r * 256, (const char*)x + r * 256, 256, qfull, (uint16_t)0xFFFF);
            int row = (b * 8 + gk) * SK + WIN0 + s * 256;
            const char* kp = (const char*)kc + (size_t)row * 512;
            uint32_t bar = kfull, dst = sb + 2 * SLOT;
#pragma unroll 1
            for (int i = 0; i < 8; i++) {
                mbar_expect_tx(bar, 16384);
                if (i >= 4) mbar_wait(empty + 8 * (i - 4));
                pace(due, i < WLK ? qfull : bar - 8 * WLK);
                bulk_g2s(dst, kp, 16384, bar);
                if (i == 1) {
                    asm volatile("prefetch.tensormap [%0];" ::"l"(&v_map) : "memory");
                    asm volatile("prefetch.tensormap [%0];" ::"l"(&wo_map) : "memory");
                }
                due += TDK;
                kp += 16384;
                bar += 8;
                dst = (i == 3) ? sb : dst + SLOT;
            }
#pragma unroll 1
            for (int k = 0; k < 16; k++) {
                mbar_expect_tx(bar, 8192);
                mbar_wait(empty + 8 * (4 + (k >> 1)));
                const int d = k - WLV;
                pace(due, vfull + 8 * (d < 0 ? (d >> 1) : d));
                tma3d(dst, &v_map, row, bar);
                due += k < 12 ? TDV : TDV2;
                row += 16;
                bar += 8;
                dst = (k == 3) ? sb : dst + 8192;
            }
            if (proj) {
                due += TGAP;
                mbar_wait(empty + 8 * 12);
                mbar_wait(empty + 8 * 13);
#pragma unroll 1
                for (int n = 0; n < 4; n++) {
                    mbar_expect_tx(bar, 8192);
                    pace(due, bar - 8 * WLO);
                    tma4d(sb + n * 8192, &wo_map, c * 64, (n + ROT(c, gk)) & 3, (2 * gk + (r >= 7)) * (64 / WG), bar);
                    due += TDO;
                    bar += 8;
                }
            }
            mbar_wait(done);
            if (spins >= SPIN_LIMIT) __trap();
        }
        return;
    }

    const int w = warp - 1, j = threadIdx.x - 32;
    const int g = lane >> 2, t = lane & 3;

    if (w < 7) {
        cluster_arrive();
        cluster_wait();
        const uint32_t qa = sb + (w * 32 + (lane >> 4) * 8 + (lane & 7)) * 128;
        const uint32_t xa = sb + OFF_OB + (g & 3) * 896 + (cta & 1) * 448 + w * 64 + t * 4;
        mbar_wait(qfull);
        const uint32_t x0 = lds32(xa), x1 = lds32(xa + 16), x2 = lds32(xa + 32), x3 = lds32(xa + 48);
        float cq[4][4];
#pragma unroll
        for (int m = 0; m < 4; m++) {
            const uint32_t a = qa + (((2 * m + ((lane >> 3) & 1)) ^ (lane & 7)) << 4);
            const uint4 f0 = ldsm4t(a), f1 = ldsm4t(a + 2048);
            cq[m][0] = cq[m][1] = cq[m][2] = cq[m][3] = 0.f;
            mma16816(cq[m], f0, x0, x1);
            mma16816(cq[m], f1, x2, x3);
        }
        slot_release(empty + 8 * (w >> 2), fu(cq[0][0]) ^ fu(cq[1][0]) ^ fu(cq[2][0]) ^ fu(cq[3][0]), zero, lane);
        const int hf = t >> 1;
        const uint32_t qr = sb + OFF_QRED + w * 1024 + (t & 1) * 512 + hf * 128 + g * 16;
        sts128f(qr, hf ? cq[0][2] : cq[0][0], hf ? cq[1][2] : cq[1][0], hf ? cq[2][2] : cq[2][0], hf ? cq[3][2] : cq[3][0]);
        sts128f(qr + 256, hf ? cq[0][3] : cq[0][1], hf ? cq[1][3] : cq[1][1], hf ? cq[2][3] : cq[2][1], hf ? cq[3][3] : cq[3][1]);
    } else {
        if (lane == 0) {
#pragma unroll
            for (int i = 0; i < 28; i++) mbar_init(kfull + 8 * i, 1);
#pragma unroll
            for (int i = 0; i < 14; i++) mbar_init(empty + 8 * i, i == 1 ? 3 : (i < 10 ? 4 : 8));
#pragma unroll
            for (int i = 0; i < 7; i++) mbar_init(qbar + 8 * i, 1);
            mbar_init(done, 8);
            mbar_expect_tx(qbar, 4096);
            mbar_expect_tx(stbar, 64);
            mbar_expect_tx(obar, 2048);
#pragma unroll
            for (int i = 0; i < 4; i++) mbar_expect_tx(hbar + 8 * i, 512);
            fence_mbar_init();
        }
        __syncwarp();
        cluster_arrive();
        cluster_wait();
    }
    bar_compute();
    {
        const int pk = j >> 2;
        const uint32_t ra = sb + OFF_QRED + pk * 16;
        float4 a = lds128f(ra);
#pragma unroll
        for (int ww = 1; ww < 7; ww++) {
            const float4 v = lds128f(ra + ww * 1024);
            a.x += v.x; a.y += v.y; a.z += v.z; a.w += v.w;
        }
        const uint32_t dst = (pk >> 4) * 4 + (j & 3);
        st_async128(mapa(sb + OFF_QBUF + (r & 1) * 2048 + (r >> 1) * 256 + (pk & 15) * 16, dst),
                    fu(a.x), fu(a.y), fu(a.z), fu(a.w), mapa(qbar, dst));
        mbar_wait(qbar);
        const uint32_t qb = sb + OFF_QBUF + (j >> 5) * 256 + (j & 7) * 32 + ((j >> 3) & 3) * 4;
        const float q0 = lds32f(qb) + lds32f(qb + 2048), q1 = lds32f(qb + 16) + lds32f(qb + 2064);
        sts32(sb + OFF_QS + ((j >> 5) & 3) * 256 + (j & 1) * 128 + (j >> 7) * 64 + ((j >> 2) & 3) * 16 + ((j >> 4) & 1) * 8 + ((j >> 1) & 1) * 4,
              pack_bf16(q0, q1));
    }
    bar_compute();

    float s0 = 0.f, s1 = 0.f;
    {
        uint2 qf[8];
        const uint32_t qa = sb + OFF_QS + (g >> 2) * 128 + (g & 1) * 64 + t * 16;
        const uint32_t qx = ((g >> 1) & 1) * 8;
#pragma unroll
        for (int i = 0; i < 8; i++) qf[i] = lds64(qa + (i >> 1) * 256 + (((i & 1) * 8) ^ qx));
        const uint32_t kx = (g & 1) * 64;
        const uint32_t krow = sb + ((w & 3) * 8 + g) * 512 + t * 16;
        const int src = (lane & 28) + (g & 1);
#pragma unroll 1
        for (int k = 0; k < 4; k++) {
            const int ch = 2 * k + (w >> 2);
            const uint32_t ka = krow + (ch >= 4 ? ch - 4 : ch + 2) * SLOT;
            mbar_wait(kfull + 8 * ch);
            float a0[4] = {0.f, 0.f, 0.f, 0.f}, a1[4] = {0.f, 0.f, 0.f, 0.f};
#pragma unroll
            for (int i = 0; i < 8; i += 2) {
                const uint4 r0 = lds128(ka + ((i * 64) ^ kx)), r1 = lds128(ka + (((i + 1) * 64) ^ kx));
                mma16816(a0, r0, qf[i].x, qf[i].y);
                mma16816(a1, r1, qf[i + 1].x, qf[i + 1].y);
            }
            const float e0 = __shfl_sync(0xffffffffu, a0[0] + a1[0], src) + __shfl_sync(0xffffffffu, a0[2] + a1[2], src + 2);
            const float e1 = __shfl_sync(0xffffffffu, a0[1] + a1[1], src) + __shfl_sync(0xffffffffu, a0[3] + a1[3], src + 2);
            slot_release(empty + 8 * (2 + ch), fu(e0), zero, lane);
            if (t == k) { s0 = e0; s1 = e1; }
        }
    }
    float Mown;
    {
        const float kscale = 0.0625f * 1.4426950408889634f;
        s0 = round_bf16(s0) * kscale;
        s1 = round_bf16(s1) * kscale;
        float m0 = s0, m1 = s1;
#pragma unroll
        for (int o = 16; o > 0; o >>= 1) {
            m0 = fmaxf(m0, __shfl_xor_sync(0xffffffffu, m0, o));
            m1 = fmaxf(m1, __shfl_xor_sync(0xffffffffu, m1, o));
        }
        if (lane < 2) sts32(sb + OFF_WST + (w * 2 + lane) * 4, fu(lane ? m1 : m0));
        bar_compute();
        const float4 u0 = lds128f(sb + OFF_WST), u1 = lds128f(sb + OFF_WST + 16), u2 = lds128f(sb + OFF_WST + 32), u3 = lds128f(sb + OFF_WST + 48);
        const float M0 = fmaxf(fmaxf(fmaxf(u0.x, u0.z), fmaxf(u1.x, u1.z)), fmaxf(fmaxf(u2.x, u2.z), fmaxf(u3.x, u3.z)));
        const float M1 = fmaxf(fmaxf(fmaxf(u0.y, u0.w), fmaxf(u1.y, u1.w)), fmaxf(fmaxf(u2.y, u2.w), fmaxf(u3.y, u3.w)));
        Mown = (t & 1) ? M1 : M0;
        const uint32_t p = pack_bf16(ex2(s0 - M0), ex2(s1 - M1));
        const uint32_t pa = sb + OFF_PS + (4 * t + (w >> 1)) * 64 + (g >> 1) * 8 + (w & 1) * 4 + (g & 1) * 2;
        sts16(pa, (unsigned short)(p & 0xFFFFu));
        sts16(pa + 32, (unsigned short)(p >> 16));
        float l0 = __uint_as_float(p << 16), l1 = __uint_as_float(p & 0xFFFF0000u);
#pragma unroll
        for (int o = 16; o > 0; o >>= 1) {
            l0 += __shfl_xor_sync(0xffffffffu, l0, o);
            l1 += __shfl_xor_sync(0xffffffffu, l1, o);
        }
        if (lane < 2) sts32(sb + OFF_WST + 64 + (w * 2 + lane) * 4, fu(lane ? l1 : l0));
        bar_compute();
        if (j < 4) {
            const float4 v0 = lds128f(sb + OFF_WST + 64), v1 = lds128f(sb + OFF_WST + 80), v2 = lds128f(sb + OFF_WST + 96), v3 = lds128f(sb + OFF_WST + 112);
            const float L0 = ((v0.x + v0.z) + (v1.x + v1.z)) + ((v2.x + v2.z) + (v3.x + v3.z));
            const float L1 = ((v0.y + v0.w) + (v1.y + v1.w)) + ((v2.y + v2.w) + (v3.y + v3.w));
            st_async128(mapa(sb + OFF_WST + 128 + s * 16, b * 4 + j), fu(M0), fu(L0), fu(M1), fu(L1), mapa(stbar, b * 4 + j));
        }
    }

    const uint32_t h1_dst = pin(mapa(sb + OFF_HOP + r * 128 + (t >> 1) * 64 + g * 8, (t & 1) * 8 + w));
    const uint32_t h1_bar = pin(mapa(hbar + 8 * b, (t & 1) * 8 + w));
    const uint32_t h2_grp = (w >> 2) * 4 + (lane >> 3);
    const uint32_t h2_rank = h2_grp < 7 ? (r >> 3) * 7 + h2_grp : 14 + (r >> 3);
    const uint32_t h2_row = (r & 7) * 2 + ((lane >> 2) & 1);
    const uint32_t h2_set = WG == 16 ? (h2_row & 3) : (WG == 32 ? ((h2_row >> 1) & 3) : (h2_row >> 2));
    const uint32_t h2_pos = WG == 16 ? (h2_row >> 2) : (WG == 32 ? ((h2_row >> 3) * 2 + (h2_row & 1)) : (h2_row & 3));
    const uint32_t h2_dst = pin(mapa(sb + OFF_OB + (w & 3) * OB_STRIDE + ((h2_set - ROT(h2_grp, gk)) & 3) * 128 + (h2_pos >> 1) * 64 + (lane & 3) * 16 + (h2_pos & 1) * 8, h2_rank));
    const uint32_t h2_bar = pin(mapa(obar, h2_rank));
    const uint32_t h2_src = pin(sb + OFF_HOP + (w & 3) * 512 + (lane & 7) * 16);
    const uint32_t h2_wait = pin(hbar + 8 * (w & 3));
    const uint32_t bars = pin(obar);
    const uint32_t wo_src = pin(sb + (((lane >> 3) & 1) * 16 + (lane >> 4) * 8 + (lane & 7)) * 128 + ((w ^ (lane & 7)) << 4));
    const uint32_t ob_src = pin(sb + OFF_OB + (g & 3) * OB_STRIDE + (g >> 2) * 64 + t * 16);
    unsigned long long* acc_p = pin_ptr(acc + (c * 16 + (j >> 4)) * 32 + (j & 15));
    __nv_bfloat16* out_p = pin_ptr(out + (g & 3) * 448 + c * 64 + w * 8 + 2 * t + (g >> 2));
    const uint32_t k_one = pin(zero + 1u);
    const bool t_hi = pin(t >> 1) != 0, g_hi = pin(g >> 2) != 0, proj_on = pin(proj ? 1u : 0u) != 0;

    float acc0[4] = {0.f, 0.f, 0.f, 0.f}, acc1[4] = {0.f, 0.f, 0.f, 0.f};
    float wgt;
    {
        const uint32_t va0 = pin(sb + (w >> 1) * 2048 + ((lane >> 4) * 8 + (lane & 7)) * 128 + ((((w & 1) * 4 + ((lane >> 3) & 1)) ^ (lane & 7)) << 4));
        const uint32_t va1 = pin(va0 ^ 32);
        const uint32_t pa = pin(sb + OFF_PS + ((g >> 1) & 1) * 32 + t * 8);
        const uint32_t vb = bars - (obar - vfull);
#pragma unroll 1
        for (int k = 0; k < 8; k += 2) {
            const uint32_t so = (k < 4 ? k + 8 : k - 4) * 8192;
            const uint2 p0 = lds64(pa + k * 64), p1 = lds64(pa + k * 64 + 64);
            mbar_wait(vb + 8 * k);
            const uint4 f0 = ldsm4t(va0 + so), f1 = ldsm4t(va1 + so);
            mma16816(acc0, f0, p0.x, p0.y);
            mma16816(acc1, f1, p0.x, p0.y);
            mbar_wait(vb + 8 * k + 8);
            const uint4 f2 = ldsm4t(va0 + so + 8192), f3 = ldsm4t(va1 + so + 8192);
            mma16816(acc0, f2, p1.x, p1.y);
            mma16816(acc1, f3, p1.x, p1.y);
            slot_release(empty + 8 * (10 + (k >> 1)), fu(acc0[0]) ^ fu(acc1[0]), zero, lane);
        }
        uint2 pw[8];
#pragma unroll
        for (int k = 8; k < 16; k++) pw[k - 8] = lds64(pa + k * 64);
        {
            mbar_wait(stbar);
            const uint32_t sa = sb + OFF_WST + 128 + (t & 1) * 8;
            const float2 z0 = lds64f(sa), z1 = lds64f(sa + 16), z2 = lds64f(sa + 32), z3 = lds64f(sa + 48);
            const float mx = fmaxf(fmaxf(z0.x, z1.x), fmaxf(z2.x, z3.x));
            const float W = (ex2(z0.x - mx) * z0.y + ex2(z1.x - mx) * z1.y) + (ex2(z2.x - mx) * z2.y + ex2(z3.x - mx) * z3.y);
            wgt = __uint_as_float(pin(fu(__fdividef(ex2(Mown - mx), W))));
        }
        uint4 f0, f1;
#pragma unroll
        for (int k = 8; k < 16; k++) {
            mbar_wait_fast(vb + 8 * k);
            if (k == 15) GT_AT(1);
            const uint4 n0 = ldsm4t(va0 + (k - 4) * 8192), n1 = ldsm4t(va1 + (k - 4) * 8192);
            if (k > 8) {
                mma16816(acc0, f0, pw[k - 9].x, pw[k - 9].y);
                mma16816(acc1, f1, pw[k - 9].x, pw[k - 9].y);
            }
            f0 = n0; f1 = n1;
        }
        mma16816(acc0, f0, pw[7].x, pw[7].y);
        mma16816(acc1, f1, pw[7].x, pw[7].y);
    }
    st_async64(h1_dst, fu((t_hi ? acc1[0] : acc0[0]) * wgt), fu((t_hi ? acc1[2] : acc0[2]) * wgt), h1_bar);
    {
        mbar_wait_fast(h2_wait);
        const float4 v0 = lds128f(h2_src), v1 = lds128f(h2_src + 128), v2 = lds128f(h2_src + 256), v3 = lds128f(h2_src + 384);
        st_async64(h2_dst, pack_bf16((v0.x + v1.x) + (v2.x + v3.x), (v0.z + v1.z) + (v2.z + v3.z)),
                   pack_bf16((v0.y + v1.y) + (v2.y + v3.y), (v0.w + v1.w) + (v2.w + v3.w)), h2_bar);
    }
    if (!proj_on) {
        mbar_wait_fast(bars);
        slot_release(bars + (done - obar), 0u, 0u, lane);
        GT_END();
        return;
    }
    float sum;
    {
        const uint32_t ob = bars - (obar - ofull);
        float x0[4] = {0.f, 0.f, 0.f, 0.f}, x1[4] = {0.f, 0.f, 0.f, 0.f}, y0[4] = {0.f, 0.f, 0.f, 0.f}, y1[4] = {0.f, 0.f, 0.f, 0.f};
        uint4 bp[4], bq[4], oa[4];
#pragma unroll
        for (int n = 0; n < 3; n++) {
            mbar_wait_fast(ob + 8 * n);
            bp[n] = ldsm4t(wo_src + n * 8192);
            bq[n] = ldsm4t(wo_src + n * 8192 + 4096);
        }
        mbar_wait_fast(bars);
        GT_AT(5);
#pragma unroll
        for (int n = 0; n < 4; n++) oa[n] = lds128(ob_src + n * 128);
#pragma unroll
        for (int n = 0; n < 4; n++) {
            if (n == 3) {
                mbar_wait_fast(ob + 24);
                GT_AT(4);
                bp[3] = ldsm4t(wo_src + 3 * 8192);
                bq[3] = ldsm4t(wo_src + 3 * 8192 + 4096);
            }
            mma16816(x0, oa[n], bp[n].x, bp[n].y);
            mma16816(y0, oa[n], bp[n].z, bp[n].w);
            mma16816(x1, oa[n], bq[n].x, bq[n].y);
            mma16816(y1, oa[n], bq[n].z, bq[n].w);
        }
        float keep = x0[0] + y0[2], send = x0[1] + y0[3];
        if (g_hi) { send = x1[0] + y1[2]; keep = x1[1] + y1[3]; }
        sum = keep + __shfl_xor_sync(0xffffffffu, send, 16);
    }
    const uint32_t bits = fu(sum);
    const uint32_t sh = 129u - ((bits >> 23) & 0xFFu);
    const uint32_t smant = (((bits << 3) & 0x3FFFFF8u) | 0x4000000u) ^ (uint32_t)((int)bits >> 31);
    long long fx;
    asm("shr.s64 %0, %1, %2;" : "=l"(fx) : "l"((long long)((unsigned long long)smant << 32)), "r"(sh));
    const unsigned long long inc = ((unsigned long long)fx & 0xFFFFFFFF00000000ull) | (((uint32_t)fx & ~0x3FFu) | k_one);
    const bool fast = __any_sync(0xffffffffu, fabsf(sum) >= 0x1p-22f) && fabsf(sum) < 8.0f;
    GT_AT(7);
    unsigned long long tot = 0ull;
    asm volatile("{\n.reg .pred p;\nsetp.ne.u32 p, %3, 0;\n@p atom.relaxed.gpu.global.add.u64 %0, [%1], %2;\n}"
                 : "+l"(tot) : "l"(acc_p), "l"(inc), "r"((uint32_t)fast) : "memory");
    slot_release(bars + (done - obar), 0u, 0u, lane);
    if (!fast) { accumulate_slow(sum, acc_p, out_p); return; }
    tot += inc;
    const uint32_t cnt = (uint32_t)tot & 0x3FFu;
    asm volatile("{\n.reg .pred p;\nsetp.eq.u32 p, %3, 16;\n@p st.global.u16 [%0], %1;\n@p st.global.u64 [%2], 0;\n}"
                 ::"l"(out_p), "h"(__bfloat16_as_ushort(__float2bfloat16(acc_value(tot)))), "l"(acc_p), "r"(cnt) : "memory");
    if (cnt > 16u) finish_with_side(tot, acc_p, out_p);
    GT_END();
}

typedef CUresult (*EncodeFn)(CUtensorMap*, CUtensorMapDataType, cuuint32_t, void*, const cuuint64_t*, const cuuint64_t*,
                             const cuuint32_t*, const cuuint32_t*, CUtensorMapInterleave, CUtensorMapSwizzle,
                             CUtensorMapL2promotion, CUtensorMapFloatOOBfill);

}

extern "C" void kernel_launch(void* const* d_in, const int* in_sizes, int n_in, void* d_out, int out_size) {
    (void)in_sizes; (void)n_in; (void)out_size;
    static EncodeFn encode = nullptr;
    static void* acc = nullptr;
    if (!encode) {
        cudaDriverEntryPointQueryResult qr;
        cudaGetDriverEntryPoint("cuTensorMapEncodeTiled", (void**)&encode, cudaEnableDefault, &qr);
        cudaGetSymbolAddress(&acc, g_acc);
        cudaFuncSetAttribute(decode_kernel, cudaFuncAttributeMaxDynamicSharedMemorySize, SMEM_BYTES);
        cudaFuncSetAttribute(decode_kernel, cudaFuncAttributeNonPortableClusterSizeAllowed, 1);
    }
    const cuuint32_t estr[4] = {1, 1, 1, 1};
    CUtensorMap wq_map, wo_map, v_map;
    {
        const cuuint64_t dim[2] = {4096, 448}, str[1] = {8192};
        const cuuint32_t box[2] = {64, 224};
        encode(&wq_map, CU_TENSOR_MAP_DATA_TYPE_BFLOAT16, 2, d_in[3], dim, str, box, estr, CU_TENSOR_MAP_INTERLEAVE_NONE,
               CU_TENSOR_MAP_SWIZZLE_128B, CU_TENSOR_MAP_L2_PROMOTION_NONE, CU_TENSOR_MAP_FLOAT_OOB_FILL_NONE);
    }
    {
        const cuuint64_t dim[4] = {448, WG, 4, 4096 / (4 * WG)}, str[3] = {896, 896 * WG, 896 * WG * 4};
        const cuuint32_t box[4] = {64, WG, 1, 64 / WG};
        encode(&wo_map, CU_TENSOR_MAP_DATA_TYPE_BFLOAT16, 4, d_in[4], dim, str, box, estr, CU_TENSOR_MAP_INTERLEAVE_NONE,
               CU_TENSOR_MAP_SWIZZLE_128B, CU_TENSOR_MAP_L2_PROMOTION_NONE, CU_TENSOR_MAP_FLOAT_OOB_FILL_NONE);
    }
    {
        const cuuint64_t dim[3] = {64, 4ull * 8 * SK, 4}, str[2] = {512, 128};
        const cuuint32_t box[3] = {64, 16, 4};
        encode(&v_map, CU_TENSOR_MAP_DATA_TYPE_BFLOAT16, 3, d_in[2], dim, str, box, estr, CU_TENSOR_MAP_INTERLEAVE_NONE,
               CU_TENSOR_MAP_SWIZZLE_128B, CU_TENSOR_MAP_L2_PROMOTION_NONE, CU_TENSOR_MAP_FLOAT_OOB_FILL_NONE);
    }
    cudaLaunchConfig_t cfg = {};
    cfg.gridDim = dim3(128);
    cfg.blockDim = dim3(NTHREADS);
    cfg.dynamicSmemBytes = SMEM_BYTES;
    cfg.stream = cudaStreamPerThread;
    cudaLaunchAttribute attr[2];
    attr[0].id = cudaLaunchAttributeClusterDimension;
    attr[0].val.clusterDim.x = 16; attr[0].val.clusterDim.y = 1; attr[0].val.clusterDim.z = 1;
    attr[1].id = cudaLaunchAttributeClusterSchedulingPolicyPreference;
    attr[1].val.clusterSchedulingPolicyPreference = cudaClusterSchedulingPolicyLoadBalancing;
    cfg.attrs = attr;
    cfg.numAttrs = 2;
    cudaLaunchKernelEx(&cfg, decode_kernel, (const __nv_bfloat16*)d_in[0], (const __nv_bfloat16*)d_in[1],
                       (const __nv_bfloat16*)d_in[3], (__nv_bfloat16*)d_out, (unsigned long long*)acc, 0u,
                       wq_map, wo_map, v_map);
}
```

```cpp
#include <cuda_runtime.h>
#include <cuda_bf16.h>
#include <cuda.h>
#include <stdint.h>

namespace {

constexpr int SK = 4096, WIN0 = 3072;
constexpr int SLOT = 16384;
constexpr int OFF_BAR  = 6 * SLOT;
constexpr int OFF_QBUF = OFF_BAR + 416;
constexpr int OFF_QS   = OFF_QBUF + 4096;
constexpr int OFF_WST  = OFF_QS + 1024;
constexpr int OB_STRIDE = 576;
constexpr int OFF_OB   = OFF_WST + 192;
constexpr int OFF_HOP  = OFF_OB + 4 * OB_STRIDE;
constexpr int OFF_QRED = OFF_HOP + 2048;
constexpr int OFF_PS   = OFF_QRED;
constexpr int SMEM_BYTES = OFF_QRED + 7 * 1024;
static_assert(SMEM_BYTES <= 115712, "two CTAs must fit on one SM");
constexpr int NTHREADS = 288;
constexpr int SPIN_LIMIT = 1 << 20;

constexpr int T_K0   = 455;
constexpr int T_K    = 662;
constexpr int T_V    = 348;
constexpr int T_V2   = 270;
constexpr int T_GAP  = 30;
constexpr int T_O    = 300;
constexpr int T_LEAD = 1600;
constexpr int MIN_K = 2, MIN_V = 4;
constexpr int MAX_O = 6;

constexpr int ACC_WORDS = 1792 * 2;
__device__ __align__(1024) unsigned long long g_acc[ACC_WORDS];
__device__ float g_side[ACC_WORDS];

__device__ __forceinline__ void mbar_init(uint32_t bar, uint32_t cnt) {
    asm volatile("mbarrier.init.shared::cta.b64 [%0], %1;" ::"r"(bar), "r"(cnt) : "memory");
}
__device__ __forceinline__ void mbar_expect_tx(uint32_t bar, uint32_t bytes) {
    asm volatile("mbarrier.arrive.expect_tx.shared::cta.b64 _, [%0], %1;" ::"r"(bar), "r"(bytes) : "memory");
}
__device__ __forceinline__ void slot_release(uint32_t bar, uint32_t dep, uint32_t zero, int lane) {
    if (lane == 0) asm volatile("mbarrier.arrive.shared::cta.b64 _, [%0];" ::"r"(bar + (dep & zero)) : "memory");
}
__device__ __forceinline__ void mbar_wait_n(uint32_t bar, uint32_t& n) {
    asm volatile("{\n.reg .pred p, q;\n"
                 "WAIT_LOOP:\n"
                 "mbarrier.try_wait.parity.shared::cta.b64 p, [%1], 0;\n"
                 "add.u32 %0, %0, 1;\n"
                 "setp.lt.and.u32 q, %0, %2, !p;\n"
                 "@q bra.uni WAIT_LOOP;\n}"
                 : "+r"(n) : "r"(bar), "n"(SPIN_LIMIT) : "memory");
}
#define mbar_wait(bar) mbar_wait_n(bar, spins)
__device__ __forceinline__ void mbar_wait_fast(uint32_t bar) {
    asm volatile("{\n.reg .pred p;\nWAIT_LOOP:\nmbarrier.try_wait.parity.shared::cta.b64 p, [%0], 0;\n@!p bra.uni WAIT_LOOP;\n}"
                 ::"r"(bar) : "memory");
}
__device__ __forceinline__ uint32_t now_ns() {
    uint32_t t;
    asm volatile("mov.u32 %0, %%globaltimer_lo;" : "=r"(t)::"memory");
    return t;
}
__device__ __forceinline__ void pace(uint32_t due, uint32_t bar) {
    while ((int)(now_ns() - due) < 0) {
        uint32_t ok;
        asm volatile("{\n.reg .pred p;\nmbarrier.test_wait.parity.shared::cta.b64 p, [%1], 0;\nselp.u32 %0, 1, 0, p;\n}"
                     : "=r"(ok) : "r"(bar) : "memory");
        if (ok) break;
    }
}
__device__ __forceinline__ void bulk_g2s(uint32_t dst, const void* src, uint32_t bytes, uint32_t bar) {
    asm volatile("cp.async.bulk.shared::cluster.global.mbarrier::complete_tx::bytes [%0], [%1], %2, [%3];"
                 ::"r"(dst), "l"(src), "r"(bytes), "r"(bar) : "memory");
}
__device__ __forceinline__ void bulk_g2s_mc(uint32_t dst, const void* src, uint32_t bytes, uint32_t bar, uint16_t mask) {
    asm volatile("cp.async.bulk.shared::cluster.global.mbarrier::complete_tx::bytes.multicast::cluster [%0], [%1], %2, [%3], %4;"
                 ::"r"(dst), "l"(src), "r"(bytes), "r"(bar), "h"(mask) : "memory");
}
__device__ __forceinline__ void tma2d(uint32_t dst, const CUtensorMap* tm, int c0, int c1, uint32_t bar) {
    asm volatile("cp.async.bulk.tensor.2d.shared::cluster.global.mbarrier::complete_tx::bytes [%0], [%1, {%3, %4}], [%2];"
                 ::"r"(dst), "l"(tm), "r"(bar), "r"(c0), "r"(c1) : "memory");
}
__device__ __forceinline__ void tma3d(uint32_t dst, const CUtensorMap* tm, int c1, uint32_t bar) {
    asm volatile("cp.async.bulk.tensor.3d.shared::cluster.global.mbarrier::complete_tx::bytes [%0], [%1, {%3, %4, %3}], [%2];"
                 ::"r"(dst), "l"(tm), "r"(bar), "r"(0), "r"(c1) : "memory");
}
__device__ __forceinline__ void tma4d(uint32_t dst, const CUtensorMap* tm, int c0, int c2, int c3, uint32_t bar) {
    asm volatile("cp.async.bulk.tensor.4d.shared::cluster.global.mbarrier::complete_tx::bytes [%0], [%1, {%3, %4, %5, %6}], [%2];"
                 ::"r"(dst), "l"(tm), "r"(bar), "r"(c0), "r"(0), "r"(c2), "r"(c3) : "memory");
}
__device__ __forceinline__ uint32_t pin(uint32_t v) {
    uint32_t o;
    asm volatile("shfl.sync.bfly.b32 %0, %1, 0, 0x1f, 0xffffffff;" : "=r"(o) : "r"(v));
    return o;
}
template <typename T> __device__ __forceinline__ T* pin_ptr(T* p) {
    const unsigned long long a = (unsigned long long)p;
    return (T*)(((unsigned long long)pin((uint32_t)(a >> 32)) << 32) | pin((uint32_t)a));
}
__device__ __forceinline__ bool elect_one() {
    uint32_t p;
    asm volatile("{\n.reg .pred P;\nelect.sync _|P, 0xffffffff;\nselp.u32 %0, 1, 0, P;\n}" : "=r"(p));
    return p != 0;
}
__device__ __forceinline__ void bar_compute() { asm volatile("bar.sync 1, 256;" ::: "memory"); }
__device__ __forceinline__ void cluster_arrive() { asm volatile("barrier.cluster.arrive.relaxed.aligned;" ::: "memory"); }
__device__ __forceinline__ void cluster_wait() { asm volatile("barrier.cluster.wait.aligned;" ::: "memory"); }
__device__ __forceinline__ void fence_mbar_init() { asm volatile("fence.mbarrier_init.release.cluster;" ::: "memory"); }
__device__ __forceinline__ uint32_t mapa(uint32_t a, uint32_t rank) {
    uint32_t o;
    asm("mapa.shared::cluster.u32 %0, %1, %2;" : "=r"(o) : "r"(a), "r"(rank));
    return o;
}
__device__ __forceinline__ void st_async128(uint32_t a, uint32_t x, uint32_t y, uint32_t z, uint32_t w, uint32_t bar) {
    asm volatile("st.async.shared::cluster.mbarrier::complete_tx::bytes.v4.b32 [%0], {%1,%2,%3,%4}, [%5];"
                 ::"r"(a), "r"(x), "r"(y), "r"(z), "r"(w), "r"(bar) : "memory");
}
__device__ __forceinline__ void st_async64(uint32_t a, uint32_t x, uint32_t y, uint32_t bar) {
    asm volatile("st.async.shared::cluster.mbarrier::complete_tx::bytes.v2.b32 [%0], {%1,%2}, [%3];"
                 ::"r"(a), "r"(x), "r"(y), "r"(bar) : "memory");
}
__device__ __forceinline__ void mma16816(float (&c)[4], const uint4& a, uint32_t b0, uint32_t b1) {
    asm volatile("mma.sync.aligned.m16n8k16.row.col.f32.bf16.bf16.f32 {%0,%1,%2,%3}, {%4,%5,%6,%7}, {%8,%9}, {%0,%1,%2,%3};"
                 : "+f"(c[0]), "+f"(c[1]), "+f"(c[2]), "+f"(c[3])
                 : "r"(a.x), "r"(a.y), "r"(a.z), "r"(a.w), "r"(b0), "r"(b1));
}
__device__ __forceinline__ uint4 lds128(uint32_t a) {
    uint4 v;
    asm volatile("ld.shared.v4.u32 {%0,%1,%2,%3}, [%4];" : "=r"(v.x), "=r"(v.y), "=r"(v.z), "=r"(v.w) : "r"(a) : "memory");
    return v;
}
__device__ __forceinline__ float4 lds128f(uint32_t a) {
    float4 v;
    asm volatile("ld.shared.v4.f32 {%0,%1,%2,%3}, [%4];" : "=f"(v.x), "=f"(v.y), "=f"(v.z), "=f"(v.w) : "r"(a) : "memory");
    return v;
}
__device__ __forceinline__ float2 lds64f(uint32_t a) {
    float2 v;
    asm volatile("ld.shared.v2.f32 {%0,%1}, [%2];" : "=f"(v.x), "=f"(v.y) : "r"(a) : "memory");
    return v;
}
__device__ __forceinline__ uint2 lds64(uint32_t a) {
    uint2 v;
    asm volatile("ld.shared.v2.u32 {%0,%1}, [%2];" : "=r"(v.x), "=r"(v.y) : "r"(a) : "memory");
    return v;
}
__device__ __forceinline__ uint32_t lds32(uint32_t a) {
    uint32_t v;
    asm volatile("ld.shared.u32 %0, [%1];" : "=r"(v) : "r"(a) : "memory");
    return v;
}
__device__ __forceinline__ float lds32f(uint32_t a) { return __uint_as_float(lds32(a)); }
__device__ __forceinline__ void sts128f(uint32_t a, float x, float y, float z, float w) {
    asm volatile("st.shared.v4.f32 [%0], {%1,%2,%3,%4};" ::"r"(a), "f"(x), "f"(y), "f"(z), "f"(w) : "memory");
}
__device__ __forceinline__ void sts32(uint32_t a, uint32_t v) {
    asm volatile("st.shared.u32 [%0], %1;" ::"r"(a), "r"(v) : "memory");
}
__device__ __forceinline__ void sts16(uint32_t a, unsigned short v) {
    asm volatile("st.shared.u16 [%0], %1;" ::"r"(a), "h"(v) : "memory");
}
__device__ __forceinline__ uint4 ldsm4t(uint32_t a) {
    uint4 v;
    asm volatile("ldmatrix.sync.aligned.m8n8.x4.trans.shared.b16 {%0,%1,%2,%3}, [%4];"
                 : "=r"(v.x), "=r"(v.y), "=r"(v.z), "=r"(v.w) : "r"(a) : "memory");
    return v;
}
__device__ __forceinline__ uint32_t pack_bf16(float lo, float hi) {
    uint32_t r;
    asm("cvt.rn.bf16x2.f32 %0, %1, %2;" : "=r"(r) : "f"(hi), "f"(lo));
    return r;
}
__device__ __forceinline__ float round_bf16(float v) { return __uint_as_float(pack_bf16(0.f, v) & 0xFFFF0000u); }
__device__ __forceinline__ float ex2(float x) {
    float y;
    asm("ex2.approx.ftz.f32 %0, %1;" : "=f"(y) : "f"(x));
    return y;
}
__device__ __forceinline__ uint32_t fu(float v) { return __float_as_uint(v); }

__device__ __forceinline__ float acc_value(unsigned long long tot) {
    return fmaf((float)(int)(uint32_t)(tot >> 32), 0x1p-24f, (float)((uint32_t)tot >> 10) * 0x1p-46f);
}
__device__ __noinline__ void finish_with_side(unsigned long long tot, unsigned long long* acc_p, __nv_bfloat16* out_p) {
    if ((tot & 31ull) != 16ull) return;
    __threadfence();
    const float side = atomicExch(&g_side[acc_p - g_acc], 0.0f);
    *out_p = __float2bfloat16(acc_value(tot) + side);
    *acc_p = 0ull;
}
__device__ __noinline__ void accumulate_slow(float sum, unsigned long long* acc_p, __nv_bfloat16* out_p) {
    atomicAdd(&g_side[acc_p - g_acc], sum);
    __threadfence();
    finish_with_side(atomicAdd(acc_p, 33ull) + 33ull, acc_p, out_p);
}

__global__ void __launch_bounds__(NTHREADS, 2)
decode_kernel(const __nv_bfloat16* __restrict__ x, const __nv_bfloat16* __restrict__ kc,
              const __nv_bfloat16* __restrict__ wq, __nv_bfloat16* __restrict__ out,
              unsigned long long* __restrict__ acc, const uint32_t zero,
              const __grid_constant__ CUtensorMap wq_map, const __grid_constant__ CUtensorMap wo_map,
              const __grid_constant__ CUtensorMap v_map) {
    asm volatile("prefetch.global.L2 [%0];" ::"l"((const char*)wq + (blockIdx.x * 224 + min(threadIdx.x, 223u)) * 128));

    extern __shared__ __align__(1024) unsigned char smem[];
    const uint32_t sb = (uint32_t)__cvta_generic_to_shared(smem);
    const int warp = threadIdx.x >> 5, lane = threadIdx.x & 31;
    const int cta = blockIdx.x;
    const int gk = cta >> 4, r = cta & 15, b = r >> 2, s = r & 3;
    const bool proj = r < 14;
    const int c = r - 7 * (r >= 7);
    const uint32_t qfull = sb + OFF_BAR, kfull = qfull + 8, vfull = kfull + 64, ofull = vfull + 128, empty = ofull + 32;
    const uint32_t qbar = empty + 14 * 8, stbar = qbar + 8, obar = qbar + 16, hbar = qbar + 24, done = qbar + 56;
    uint32_t spins = 0;

    if (warp == 0) {
        const bool leader = elect_one();
        if (leader) {
            mbar_init(qfull, 1);
            mbar_expect_tx(qfull, 28672 + 3584);
            tma2d(sb, &wq_map, (cta >> 1) * 64, (cta & 1) * 224, qfull);
            fence_mbar_init();
        }
        uint32_t due = now_ns() + T_K0 - (gk == 7 ? T_LEAD : 0);
        __syncwarp();
        cluster_arrive();
        cluster_wait();
        if (leader) {
            if (proj) bulk_g2s_mc(sb + OFF_OB + r * 256, (const char*)x + r * 256, 256, qfull, (uint16_t)0xFFFF);
            int row = (b * 8 + gk) * SK + WIN0 + s * 256;
            const char* kp = (const char*)kc + (size_t)row * 512;
            uint32_t bar = kfull, dst = sb + 2 * SLOT;
#pragma unroll 1
            for (int i = 0; i < 8; i++) {
                mbar_expect_tx(bar, 16384);
                if (i >= 4) mbar_wait(empty + 8 * (i - 4));
                pace(due, i < MIN_K ? qfull : bar - 8 * MIN_K);
                bulk_g2s(dst, kp, 16384, bar);
                if (i == 1) {
                    asm volatile("prefetch.tensormap [%0];" ::"l"(&v_map) : "memory");
                    asm volatile("prefetch.tensormap [%0];" ::"l"(&wo_map) : "memory");
                }
                due += T_K;
                kp += 16384;
                bar += 8;
                dst = (i == 3) ? sb : dst + SLOT;
            }
#pragma unroll 1
            for (int k = 0; k < 16; k++) {
                mbar_expect_tx(bar, 8192);
                mbar_wait(empty + 8 * (4 + (k >> 1)));
                const int d = k - MIN_V;
                pace(due, vfull + 8 * (d < 0 ? (d >> 1) : d));
                tma3d(dst, &v_map, row, bar);
                due += k < 12 ? T_V : T_V2;
                row += 16;
                bar += 8;
                dst = (k == 3) ? sb : dst + 8192;
            }
            if (proj) {
                due += T_GAP;
                mbar_wait(empty + 8 * 12);
                mbar_wait(empty + 8 * 13);
#pragma unroll 1
                for (int n = 0; n < 4; n++) {
                    mbar_expect_tx(bar, 8192);
                    if (gk != 7) mbar_wait(bar - 8 * MAX_O);
                    pace(due, bar - 8);
                    tma4d(sb + n * 8192, &wo_map, c * 64, (n + c) & 3, (2 * gk + (r >= 7)) * 2, bar);
                    due += T_O;
                    bar += 8;
                }
            }
            mbar_wait(done);
            if (spins >= SPIN_LIMIT) __trap();
        }
        return;
    }

    const int w = warp - 1, j = threadIdx.x - 32;
    const int g = lane >> 2, t = lane & 3;

    if (w < 7) {
        cluster_arrive();
        cluster_wait();
        const uint32_t qa = sb + (w * 32 + (lane >> 4) * 8 + (lane & 7)) * 128;
        const uint32_t xa = sb + OFF_OB + (g & 3) * 896 + (cta & 1) * 448 + w * 64 + t * 4;
        mbar_wait(qfull);
        const uint32_t x0 = lds32(xa), x1 = lds32(xa + 16), x2 = lds32(xa + 32), x3 = lds32(xa + 48);
        float cq[4][4];
#pragma unroll
        for (int m = 0; m < 4; m++) {
            const uint32_t a = qa + (((2 * m + ((lane >> 3) & 1)) ^ (lane & 7)) << 4);
            const uint4 f0 = ldsm4t(a), f1 = ldsm4t(a + 2048);
            cq[m][0] = cq[m][1] = cq[m][2] = cq[m][3] = 0.f;
            mma16816(cq[m], f0, x0, x1);
            mma16816(cq[m], f1, x2, x3);
        }
        slot_release(empty + 8 * (w >> 2), fu(cq[0][0]) ^ fu(cq[1][0]) ^ fu(cq[2][0]) ^ fu(cq[3][0]), zero, lane);
        const int hf = t >> 1;
        const uint32_t qr = sb + OFF_QRED + w * 1024 + (t & 1) * 512 + hf * 128 + g * 16;
        sts128f(qr, hf ? cq[0][2] : cq[0][0], hf ? cq[1][2] : cq[1][0], hf ? cq[2][2] : cq[2][0], hf ? cq[3][2] : cq[3][0]);
        sts128f(qr + 256, hf ? cq[0][3] : cq[0][1], hf ? cq[1][3] : cq[1][1], hf ? cq[2][3] : cq[2][1], hf ? cq[3][3] : cq[3][1]);
    } else {
        if (lane == 0) {
#pragma unroll
            for (int i = 0; i < 28; i++) mbar_init(kfull + 8 * i, 1);
#pragma unroll
            for (int i = 0; i < 14; i++) mbar_init(empty + 8 * i, i == 1 ? 3 : (i < 10 ? 4 : 8));
#pragma unroll
            for (int i = 0; i < 7; i++) mbar_init(qbar + 8 * i, 1);
            mbar_init(done, 8);
            mbar_expect_tx(qbar, 4096);
            mbar_expect_tx(stbar, 64);
            mbar_expect_tx(obar, 2048);
#pragma unroll
            for (int i = 0; i < 4; i++) mbar_expect_tx(hbar + 8 * i, 512);
            fence_mbar_init();
        }
        __syncwarp();
        cluster_arrive();
        cluster_wait();
    }
    bar_compute();
    {
        const int pk = j >> 2;
        const uint32_t ra = sb + OFF_QRED + pk * 16;
        float4 a = lds128f(ra);
#pragma unroll
        for (int ww = 1; ww < 7; ww++) {
            const float4 v = lds128f(ra + ww * 1024);
            a.x += v.x; a.y += v.y; a.z += v.z; a.w += v.w;
        }
        const uint32_t dst = (pk >> 4) * 4 + (j & 3);
        st_async128(mapa(sb + OFF_QBUF + (r & 1) * 2048 + (r >> 1) * 256 + (pk & 15) * 16, dst),
                    fu(a.x), fu(a.y), fu(a.z), fu(a.w), mapa(qbar, dst));
        mbar_wait(qbar);
        const uint32_t qb = sb + OFF_QBUF + (j >> 5) * 256 + (j & 7) * 32 + ((j >> 3) & 3) * 4;
        const float q0 = lds32f(qb) + lds32f(qb + 2048), q1 = lds32f(qb + 16) + lds32f(qb + 2064);
        sts32(sb + OFF_QS + ((j >> 5) & 3) * 256 + (j & 1) * 128 + (j >> 7) * 64 + ((j >> 2) & 3) * 16 + ((j >> 4) & 1) * 8 + ((j >> 1) & 1) * 4,
              pack_bf16(q0, q1));
    }
    bar_compute();

    float s0 = 0.f, s1 = 0.f;
    {
        uint2 qf[8];
        const uint32_t qa = sb + OFF_QS + (g >> 2) * 128 + (g & 1) * 64 + t * 16;
        const uint32_t qx = ((g >> 1) & 1) * 8;
#pragma unroll
        for (int i = 0; i < 8; i++) qf[i] = lds64(qa + (i >> 1) * 256 + (((i & 1) * 8) ^ qx));
        const uint32_t kx = (g & 1) * 64;
        const uint32_t krow = sb + ((w & 3) * 8 + g) * 512 + t * 16;
        const int src = (lane & 28) + (g & 1);
#pragma unroll 1
        for (int k = 0; k < 4; k++) {
            const int ch = 2 * k + (w >> 2);
            const uint32_t ka = krow + (ch >= 4 ? ch - 4 : ch + 2) * SLOT;
            mbar_wait(kfull + 8 * ch);
            float a0[4] = {0.f, 0.f, 0.f, 0.f}, a1[4] = {0.f, 0.f, 0.f, 0.f};
#pragma unroll
            for (int i = 0; i < 8; i += 2) {
                const uint4 r0 = lds128(ka + ((i * 64) ^ kx)), r1 = lds128(ka + (((i + 1) * 64) ^ kx));
                mma16816(a0, r0, qf[i].x, qf[i].y);
                mma16816(a1, r1, qf[i + 1].x, qf[i + 1].y);
            }
            const float e0 = __shfl_sync(0xffffffffu, a0[0] + a1[0], src) + __shfl_sync(0xffffffffu, a0[2] + a1[2], src + 2);
            const float e1 = __shfl_sync(0xffffffffu, a0[1] + a1[1], src) + __shfl_sync(0xffffffffu, a0[3] + a1[3], src + 2);
            slot_release(empty + 8 * (2 + ch), fu(e0), zero, lane);
            if (t == k) { s0 = e0; s1 = e1; }
        }
    }
    float Mown;
    {
        const float kscale = 0.0625f * 1.4426950408889634f;
        s0 = round_bf16(s0) * kscale;
        s1 = round_bf16(s1) * kscale;
        float m0 = s0, m1 = s1;
#pragma unroll
        for (int o = 16; o > 0; o >>= 1) {
            m0 = fmaxf(m0, __shfl_xor_sync(0xffffffffu, m0, o));
            m1 = fmaxf(m1, __shfl_xor_sync(0xffffffffu, m1, o));
        }
        if (lane < 2) sts32(sb + OFF_WST + (w * 2 + lane) * 4, fu(lane ? m1 : m0));
        bar_compute();
        const float4 u0 = lds128f(sb + OFF_WST), u1 = lds128f(sb + OFF_WST + 16), u2 = lds128f(sb + OFF_WST + 32), u3 = lds128f(sb + OFF_WST + 48);
        const float M0 = fmaxf(fmaxf(fmaxf(u0.x, u0.z), fmaxf(u1.x, u1.z)), fmaxf(fmaxf(u2.x, u2.z), fmaxf(u3.x, u3.z)));
        const float M1 = fmaxf(fmaxf(fmaxf(u0.y, u0.w), fmaxf(u1.y, u1.w)), fmaxf(fmaxf(u2.y, u2.w), fmaxf(u3.y, u3.w)));
        Mown = (t & 1) ? M1 : M0;
        const uint32_t p = pack_bf16(ex2(s0 - M0), ex2(s1 - M1));
        const uint32_t pa = sb + OFF_PS + (4 * t + (w >> 1)) * 64 + (g >> 1) * 8 + (w & 1) * 4 + (g & 1) * 2;
        sts16(pa, (unsigned short)(p & 0xFFFFu));
        sts16(pa + 32, (unsigned short)(p >> 16));
        float l0 = __uint_as_float(p << 16), l1 = __uint_as_float(p & 0xFFFF0000u);
#pragma unroll
        for (int o = 16; o > 0; o >>= 1) {
            l0 += __shfl_xor_sync(0xffffffffu, l0, o);
            l1 += __shfl_xor_sync(0xffffffffu, l1, o);
        }
        if (lane < 2) sts32(sb + OFF_WST + 64 + (w * 2 + lane) * 4, fu(lane ? l1 : l0));
        bar_compute();
        if (j < 4) {
            const float4 v0 = lds128f(sb + OFF_WST + 64), v1 = lds128f(sb + OFF_WST + 80), v2 = lds128f(sb + OFF_WST + 96), v3 = lds128f(sb + OFF_WST + 112);
            const float L0 = ((v0.x + v0.z) + (v1.x + v1.z)) + ((v2.x + v2.z) + (v3.x + v3.z));
            const float L1 = ((v0.y + v0.w) + (v1.y + v1.w)) + ((v2.y + v2.w) + (v3.y + v3.w));
            st_async128(mapa(sb + OFF_WST + 128 + s * 16, b * 4 + j), fu(M0), fu(L0), fu(M1), fu(L1), mapa(stbar, b * 4 + j));
        }
    }

    const uint32_t h1_dst = pin(mapa(sb + OFF_HOP + r * 128 + (t >> 1) * 64 + g * 8, (t & 1) * 8 + w));
    const uint32_t h1_bar = pin(mapa(hbar + 8 * b, (t & 1) * 8 + w));
    const uint32_t h2_grp = (w >> 2) * 4 + (lane >> 3);
    const uint32_t h2_rank = h2_grp < 7 ? (r >> 3) * 7 + h2_grp : 14 + (r >> 3);
    const uint32_t h2_dst = pin(mapa(sb + OFF_OB + (w & 3) * OB_STRIDE + ((r - h2_grp) & 3) * 128 + ((r >> 2) & 1) * 64 +
                                     (lane & 3) * 16 + ((lane >> 2) & 1) * 8, h2_rank));
    const uint32_t h2_bar = pin(mapa(obar, h2_rank));
    const uint32_t h2_src = pin(sb + OFF_HOP + (w & 3) * 512 + (lane & 7) * 16);
    const uint32_t h2_wait = pin(hbar + 8 * (w & 3));
    const uint32_t bars = pin(obar);
    const uint32_t wo_src = pin(sb + (((lane >> 3) & 1) * 16 + (lane >> 4) * 8 + (lane & 7)) * 128 + ((w ^ (lane & 7)) << 4));
    const uint32_t ob_src = pin(sb + OFF_OB + (g & 3) * OB_STRIDE + (g >> 2) * 64 + t * 16);
    unsigned long long* acc_p = pin_ptr(acc + (c * 16 + (j >> 4)) * 32 + (j & 15));
    __nv_bfloat16* out_p = pin_ptr(out + (g & 3) * 448 + c * 64 + w * 8 + 2 * t + (g >> 2));
    const uint32_t k_one = pin(zero + 1u);
    const bool t_hi = pin(t >> 1) != 0, g_hi = pin(g >> 2) != 0, proj_on = pin(proj ? 1u : 0u) != 0;

    float acc0[4] = {0.f, 0.f, 0.f, 0.f}, acc1[4] = {0.f, 0.f, 0.f, 0.f};
    float wgt;
    {
        const uint32_t va0 = pin(sb + (w >> 1) * 2048 + ((lane >> 4) * 8 + (lane & 7)) * 128 + ((((w & 1) * 4 + ((lane >> 3) & 1)) ^ (lane & 7)) << 4));
        const uint32_t va1 = pin(va0 ^ 32);
        const uint32_t pa = pin(sb + OFF_PS + ((g >> 1) & 1) * 32 + t * 8);
        const uint32_t vb = bars - (obar - vfull);
#pragma unroll 1
        for (int k = 0; k < 8; k += 2) {
            const uint32_t so = (k < 4 ? k + 8 : k - 4) * 8192;
            const uint2 p0 = lds64(pa + k * 64), p1 = lds64(pa + k * 64 + 64);
            mbar_wait(vb + 8 * k);
            const uint4 f0 = ldsm4t(va0 + so), f1 = ldsm4t(va1 + so);
            mma16816(acc0, f0, p0.x, p0.y);
            mma16816(acc1, f1, p0.x, p0.y);
            mbar_wait(vb + 8 * k + 8);
            const uint4 f2 = ldsm4t(va0 + so + 8192), f3 = ldsm4t(va1 + so + 8192);
            mma16816(acc0, f2, p1.x, p1.y);
            mma16816(acc1, f3, p1.x, p1.y);
            slot_release(empty + 8 * (10 + (k >> 1)), fu(acc0[0]) ^ fu(acc1[0]), zero, lane);
        }
        uint2 pw[8];
#pragma unroll
        for (int k = 8; k < 16; k++) pw[k - 8] = lds64(pa + k * 64);
        {
            mbar_wait(stbar);
            const uint32_t sa = sb + OFF_WST + 128 + (t & 1) * 8;
            const float2 z0 = lds64f(sa), z1 = lds64f(sa + 16), z2 = lds64f(sa + 32), z3 = lds64f(sa + 48);
            const float mx = fmaxf(fmaxf(z0.x, z1.x), fmaxf(z2.x, z3.x));
            const float W = (ex2(z0.x - mx) * z0.y + ex2(z1.x - mx) * z1.y) + (ex2(z2.x - mx) * z2.y + ex2(z3.x - mx) * z3.y);
            wgt = __uint_as_float(pin(fu(__fdividef(ex2(Mown - mx), W))));
        }
        uint4 f0, f1;
#pragma unroll
        for (int k = 8; k < 16; k++) {
            mbar_wait_fast(vb + 8 * k);
            const uint4 n0 = ldsm4t(va0 + (k - 4) * 8192), n1 = ldsm4t(va1 + (k - 4) * 8192);
            if (k > 8) {
                mma16816(acc0, f0, pw[k - 9].x, pw[k - 9].y);
                mma16816(acc1, f1, pw[k - 9].x, pw[k - 9].y);
            }
            f0 = n0; f1 = n1;
        }
        mma16816(acc0, f0, pw[7].x, pw[7].y);
        mma16816(acc1, f1, pw[7].x, pw[7].y);
    }
    st_async64(h1_dst, fu((t_hi ? acc1[0] : acc0[0]) * wgt), fu((t_hi ? acc1[2] : acc0[2]) * wgt), h1_bar);
    {
        mbar_wait_fast(h2_wait);
        const float4 v0 = lds128f(h2_src), v1 = lds128f(h2_src + 128), v2 = lds128f(h2_src + 256), v3 = lds128f(h2_src + 384);
        st_async64(h2_dst, pack_bf16((v0.x + v1.x) + (v2.x + v3.x), (v0.z + v1.z) + (v2.z + v3.z)),
                   pack_bf16((v0.y + v1.y) + (v2.y + v3.y), (v0.w + v1.w) + (v2.w + v3.w)), h2_bar);
    }
    if (!proj_on) {
        mbar_wait_fast(bars);
        slot_release(bars + (done - obar), 0u, 0u, lane);
        return;
    }
    float sum;
    {
        const uint32_t ob = bars - (obar - ofull);
        float x0[4] = {0.f, 0.f, 0.f, 0.f}, x1[4] = {0.f, 0.f, 0.f, 0.f}, y0[4] = {0.f, 0.f, 0.f, 0.f}, y1[4] = {0.f, 0.f, 0.f, 0.f};
        uint4 bp[4], bq[4], oa[4];
#pragma unroll
        for (int n = 0; n < 3; n++) {
            mbar_wait_fast(ob + 8 * n);
            bp[n] = ldsm4t(wo_src + n * 8192);
            bq[n] = ldsm4t(wo_src + n * 8192 + 4096);
        }
        mbar_wait_fast(bars);
#pragma unroll
        for (int n = 0; n < 4; n++) oa[n] = lds128(ob_src + n * 128);
#pragma unroll
        for (int n = 0; n < 4; n++) {
            if (n == 3) {
                mbar_wait_fast(ob + 24);
                bp[3] = ldsm4t(wo_src + 3 * 8192);
                bq[3] = ldsm4t(wo_src + 3 * 8192 + 4096);
            }
            mma16816(x0, oa[n], bp[n].x, bp[n].y);
            mma16816(y0, oa[n], bp[n].z, bp[n].w);
            mma16816(x1, oa[n], bq[n].x, bq[n].y);
            mma16816(y1, oa[n], bq[n].z, bq[n].w);
        }
        float keep = x0[0] + y0[2], send = x0[1] + y0[3];
        if (g_hi) { send = x1[0] + y1[2]; keep = x1[1] + y1[3]; }
        sum = keep + __shfl_xor_sync(0xffffffffu, send, 16);
    }
    const uint32_t bits = fu(sum);
    const uint32_t sh = 129u - ((bits >> 23) & 0xFFu);
    const uint32_t smant = (((bits << 3) & 0x3FFFFF8u) | 0x4000000u) ^ (uint32_t)((int)bits >> 31);
    long long fx;
    asm("shr.s64 %0, %1, %2;" : "=l"(fx) : "l"((long long)((unsigned long long)smant << 32)), "r"(sh));
    const unsigned long long inc = ((unsigned long long)fx & 0xFFFFFFFF00000000ull) | (((uint32_t)fx & ~0x3FFu) | k_one);
    const bool fast = __any_sync(0xffffffffu, fabsf(sum) >= 0x1p-22f) && fabsf(sum) < 8.0f;
    unsigned long long tot = 0ull;
    asm volatile("{\n.reg .pred p;\nsetp.ne.u32 p, %3, 0;\n@p atom.relaxed.gpu.global.add.u64 %0, [%1], %2;\n}"
                 : "+l"(tot) : "l"(acc_p), "l"(inc), "r"((uint32_t)fast) : "memory");
    slot_release(bars + (done - obar), 0u, 0u, lane);
    if (!fast) { accumulate_slow(sum, acc_p, out_p); return; }
    tot += inc;
    const uint32_t cnt = (uint32_t)tot & 0x3FFu;
    asm volatile("{\n.reg .pred p;\nsetp.eq.u32 p, %3, 16;\n@p st.global.u16 [%0], %1;\n@p st.global.u64 [%2], 0;\n}"
                 ::"l"(out_p), "h"(__bfloat16_as_ushort(__float2bfloat16(acc_value(tot)))), "l"(acc_p), "r"(cnt) : "memory");
    if (cnt > 16u) finish_with_side(tot, acc_p, out_p);
}

typedef CUresult (*EncodeFn)(CUtensorMap*, CUtensorMapDataType, cuuint32_t, void*, const cuuint64_t*, const cuuint64_t*,
                             const cuuint32_t*, const cuuint32_t*, CUtensorMapInterleave, CUtensorMapSwizzle,
                             CUtensorMapL2promotion, CUtensorMapFloatOOBfill);

}

extern "C" void kernel_launch(void* const* d_in, const int* in_sizes, int n_in, void* d_out, int out_size) {
    (void)in_sizes; (void)n_in; (void)out_size;
    static EncodeFn encode = nullptr;
    static void* acc = nullptr;
    if (!encode) {
        cudaDriverEntryPointQueryResult qr;
        cudaGetDriverEntryPoint("cuTensorMapEncodeTiled", (void**)&encode, cudaEnableDefault, &qr);
        cudaGetSymbolAddress(&acc, g_acc);
        cudaFuncSetAttribute(decode_kernel, cudaFuncAttributeMaxDynamicSharedMemorySize, SMEM_BYTES);
        cudaFuncSetAttribute(decode_kernel, cudaFuncAttributeNonPortableClusterSizeAllowed, 1);
    }
    const cuuint32_t estr[4] = {1, 1, 1, 1};
    CUtensorMap wq_map, wo_map, v_map;
    {
        const cuuint64_t dim[2] = {4096, 448}, str[1] = {8192};
        const cuuint32_t box[2] = {64, 224};
        encode(&wq_map, CU_TENSOR_MAP_DATA_TYPE_BFLOAT16, 2, d_in[3], dim, str, box, estr, CU_TENSOR_MAP_INTERLEAVE_NONE,
               CU_TENSOR_MAP_SWIZZLE_128B, CU_TENSOR_MAP_L2_PROMOTION_NONE, CU_TENSOR_MAP_FLOAT_OOB_FILL_NONE);
    }
    {
        const cuuint64_t dim[4] = {448, 32, 4, 32}, str[3] = {896, 896 * 32, 896 * 128};
        const cuuint32_t box[4] = {64, 32, 1, 2};
        encode(&wo_map, CU_TENSOR_MAP_DATA_TYPE_BFLOAT16, 4, d_in[4], dim, str, box, estr, CU_TENSOR_MAP_INTERLEAVE_NONE,
               CU_TENSOR_MAP_SWIZZLE_128B, CU_TENSOR_MAP_L2_PROMOTION_NONE, CU_TENSOR_MAP_FLOAT_OOB_FILL_NONE);
    }
    {
        const cuuint64_t dim[3] = {64, 4ull * 8 * SK, 4}, str[2] = {512, 128};
        const cuuint32_t box[3] = {64, 16, 4};
        encode(&v_map, CU_TENSOR_MAP_DATA_TYPE_BFLOAT16, 3, d_in[2], dim, str, box, estr, CU_TENSOR_MAP_INTERLEAVE_NONE,
               CU_TENSOR_MAP_SWIZZLE_128B, CU_TENSOR_MAP_L2_PROMOTION_NONE, CU_TENSOR_MAP_FLOAT_OOB_FILL_NONE);
    }
    cudaLaunchConfig_t cfg = {};
    cfg.gridDim = dim3(128);
    cfg.blockDim = dim3(NTHREADS);
    cfg.dynamicSmemBytes = SMEM_BYTES;
    cfg.stream = cudaStreamPerThread;
    cudaLaunchAttribute attr[2];
    attr[0].id = cudaLaunchAttributeClusterDimension;
    attr[0].val.clusterDim.x = 16; attr[0].val.clusterDim.y = 1; attr[0].val.clusterDim.z = 1;
    attr[1].id = cudaLaunchAttributeClusterSchedulingPolicyPreference;
    attr[1].val.clusterSchedulingPolicyPreference = cudaClusterSchedulingPolicyLoadBalancing;
    cfg.attrs = attr;
    cfg.numAttrs = 2;
    cudaLaunchKernelEx(&cfg, decode_kernel, (const __nv_bfloat16*)d_in[0], (const __nv_bfloat16*)d_in[1],
                       (const __nv_bfloat16*)d_in[3], (__nv_bfloat16*)d_out, (unsigned long long*)acc, 0u,
                       wq_map, wo_map, v_map);
}
```

```cpp
#include <cuda_runtime.h>
#include <cuda_bf16.h>
#include <cuda.h>
#include <stdint.h>

namespace {

constexpr int SK = 4096, WIN0 = 3072;
constexpr int SLOT = 16384;
constexpr int OFF_BAR  = 6 * SLOT;
constexpr int OFF_QBUF = OFF_BAR + 416;
constexpr int OFF_QS   = OFF_QBUF + 4096;
constexpr int OFF_WST  = OFF_QS + 1024;
constexpr int OB_STRIDE = 576;
constexpr int OFF_OB   = OFF_WST + 192;
constexpr int OFF_HOP  = OFF_OB + 4 * OB_STRIDE;
constexpr int OFF_QRED = OFF_HOP + 2048;
constexpr int OFF_PS   = OFF_QRED;
constexpr int SMEM_BYTES = OFF_QRED + 7 * 1024;
static_assert(SMEM_BYTES <= 115712, "two CTAs must fit on one SM");
constexpr int NTHREADS = 288;
constexpr int SPIN_LIMIT = 1 << 20;

constexpr int T_K0   = 455;
constexpr int T_K    = 662;
constexpr int T_V    = 348;
constexpr int T_V2   = 270;
constexpr int T_GAP  = 30;
constexpr int T_O    = 300;
constexpr int T_LEAD = 1600;
constexpr int MIN_K = 2, MIN_V = 4;
constexpr int MAX_O = 6;

constexpr int ACC_WORDS = 1792 * 2;
__device__ __align__(1024) unsigned long long g_acc[ACC_WORDS];
__device__ float g_side[ACC_WORDS];

__device__ __forceinline__ void mbar_init(uint32_t bar, uint32_t cnt) {
    asm volatile("mbarrier.init.shared::cta.b64 [%0], %1;" ::"r"(bar), "r"(cnt) : "memory");
}
__device__ __forceinline__ void mbar_expect_tx(uint32_t bar, uint32_t bytes) {
    asm volatile("mbarrier.arrive.expect_tx.shared::cta.b64 _, [%0], %1;" ::"r"(bar), "r"(bytes) : "memory");
}
__device__ __forceinline__ void slot_release(uint32_t bar, uint32_t dep, uint32_t zero, int lane) {
    if (lane == 0) asm volatile("mbarrier.arrive.shared::cta.b64 _, [%0];" ::"r"(bar + (dep & zero)) : "memory");
}
__device__ __forceinline__ void mbar_wait_n(uint32_t bar, uint32_t& n) {
    asm volatile("{\n.reg .pred p, q;\n"
                 "WAIT_LOOP:\n"
                 "mbarrier.try_wait.parity.shared::cta.b64 p, [%1], 0;\n"
                 "add.u32 %0, %0, 1;\n"
                 "setp.lt.and.u32 q, %0, %2, !p;\n"
                 "@q bra.uni WAIT_LOOP;\n}"
                 : "+r"(n) : "r"(bar), "n"(SPIN_LIMIT) : "memory");
}
#define mbar_wait(bar) mbar_wait_n(bar, spins)
__device__ __forceinline__ void mbar_wait_fast(uint32_t bar) {
    asm volatile("{\n.reg .pred p;\nWAIT_LOOP:\nmbarrier.try_wait.parity.shared::cta.b64 p, [%0], 0;\n@!p bra.uni WAIT_LOOP;\n}"
                 ::"r"(bar) : "memory");
}
__device__ __forceinline__ uint32_t now_ns() {
    uint32_t t;
    asm volatile("mov.u32 %0, %%globaltimer_lo;" : "=r"(t)::"memory");
    return t;
}
__device__ __forceinline__ void pace(uint32_t due, uint32_t bar) {
    while ((int)(now_ns() - due) < 0) {
        uint32_t ok;
        asm volatile("{\n.reg .pred p;\nmbarrier.test_wait.parity.shared::cta.b64 p, [%1], 0;\nselp.u32 %0, 1, 0, p;\n}"
                     : "=r"(ok) : "r"(bar) : "memory");
        if (ok) break;
    }
}
__device__ __forceinline__ void bulk_g2s(uint32_t dst, const void* src, uint32_t bytes, uint32_t bar) {
    asm volatile("cp.async.bulk.shared::cluster.global.mbarrier::complete_tx::bytes [%0], [%1], %2, [%3];"
                 ::"r"(dst), "l"(src), "r"(bytes), "r"(bar) : "memory");
}
__device__ __forceinline__ void bulk_g2s_mc(uint32_t dst, const void* src, uint32_t bytes, uint32_t bar, uint16_t mask) {
    asm volatile("cp.async.bulk.shared::cluster.global.mbarrier::complete_tx::bytes.multicast::cluster [%0], [%1], %2, [%3], %4;"
                 ::"r"(dst), "l"(src), "r"(bytes), "r"(bar), "h"(mask) : "memory");
}
__device__ __forceinline__ void tma2d(uint32_t dst, const CUtensorMap* tm, int c0, int c1, uint32_t bar) {
    asm volatile("cp.async.bulk.tensor.2d.shared::cluster.global.mbarrier::complete_tx::bytes [%0], [%1, {%3, %4}], [%2];"
                 ::"r"(dst), "l"(tm), "r"(bar), "r"(c0), "r"(c1) : "memory");
}
__device__ __forceinline__ void tma3d(uint32_t dst, const CUtensorMap* tm, int c1, uint32_t bar) {
    asm volatile("cp.async.bulk.tensor.3d.shared::cluster.global.mbarrier::complete_tx::bytes [%0], [%1, {%3, %4, %3}], [%2];"
                 ::"r"(dst), "l"(tm), "r"(bar), "r"(0), "r"(c1) : "memory");
}
__device__ __forceinline__ void tma4d(uint32_t dst, const CUtensorMap* tm, int c0, int c2, int c3, uint32_t bar) {
    asm volatile("cp.async.bulk.tensor.4d.shared::cluster.global.mbarrier::complete_tx::bytes [%0], [%1, {%3, %4, %5, %6}], [%2];"
                 ::"r"(dst), "l"(tm), "r"(bar), "r"(c0), "r"(0), "r"(c2), "r"(c3) : "memory");
}
__device__ __forceinline__ uint32_t pin(uint32_t v) {
    uint32_t o;
    asm volatile("shfl.sync.bfly.b32 %0, %1, 0, 0x1f, 0xffffffff;" : "=r"(o) : "r"(v));
    return o;
}
template <typename T> __device__ __forceinline__ T* pin_ptr(T* p) {
    const unsigned long long a = (unsigned long long)p;
    return (T*)(((unsigned long long)pin((uint32_t)(a >> 32)) << 32) | pin((uint32_t)a));
}
__device__ __forceinline__ bool elect_one() {
    uint32_t p;
    asm volatile("{\n.reg .pred P;\nelect.sync _|P, 0xffffffff;\nselp.u32 %0, 1, 0, P;\n}" : "=r"(p));
    return p != 0;
}
__device__ __forceinline__ void bar_compute() { asm volatile("bar.sync 1, 256;" ::: "memory"); }
__device__ __forceinline__ void cluster_arrive() { asm volatile("barrier.cluster.arrive.relaxed.aligned;" ::: "memory"); }
__device__ __forceinline__ void cluster_wait() { asm volatile("barrier.cluster.wait.aligned;" ::: "memory"); }
__device__ __forceinline__ void fence_mbar_init() { asm volatile("fence.mbarrier_init.release.cluster;" ::: "memory"); }
__device__ __forceinline__ uint32_t mapa(uint32_t a, uint32_t rank) {
    uint32_t o;
    asm("mapa.shared::cluster.u32 %0, %1, %2;" : "=r"(o) : "r"(a), "r"(rank));
    return o;
}
__device__ __forceinline__ void st_async128(uint32_t a, uint32_t x, uint32_t y, uint32_t z, uint32_t w, uint32_t bar) {
    asm volatile("st.async.shared::cluster.mbarrier::complete_tx::bytes.v4.b32 [%0], {%1,%2,%3,%4}, [%5];"
                 ::"r"(a), "r"(x), "r"(y), "r"(z), "r"(w), "r"(bar) : "memory");
}
__device__ __forceinline__ void st_async64(uint32_t a, uint32_t x, uint32_t y, uint32_t bar) {
    asm volatile("st.async.shared::cluster.mbarrier::complete_tx::bytes.v2.b32 [%0], {%1,%2}, [%3];"
                 ::"r"(a), "r"(x), "r"(y), "r"(bar) : "memory");
}
__device__ __forceinline__ void mma16816(float (&c)[4], const uint4& a, uint32_t b0, uint32_t b1) {
    asm volatile("mma.sync.aligned.m16n8k16.row.col.f32.bf16.bf16.f32 {%0,%1,%2,%3}, {%4,%5,%6,%7}, {%8,%9}, {%0,%1,%2,%3};"
                 : "+f"(c[0]), "+f"(c[1]), "+f"(c[2]), "+f"(c[3])
                 : "r"(a.x), "r"(a.y), "r"(a.z), "r"(a.w), "r"(b0), "r"(b1));
}
__device__ __forceinline__ uint4 lds128(uint32_t a) {
    uint4 v;
    asm volatile("ld.shared.v4.u32 {%0,%1,%2,%3}, [%4];" : "=r"(v.x), "=r"(v.y), "=r"(v.z), "=r"(v.w) : "r"(a) : "memory");
    return v;
}
__device__ __forceinline__ float4 lds128f(uint32_t a) {
    float4 v;
    asm volatile("ld.shared.v4.f32 {%0,%1,%2,%3}, [%4];" : "=f"(v.x), "=f"(v.y), "=f"(v.z), "=f"(v.w) : "r"(a) : "memory");
    return v;
}
__device__ __forceinline__ float2 lds64f(uint32_t a) {
    float2 v;
    asm volatile("ld.shared.v2.f32 {%0,%1}, [%2];" : "=f"(v.x), "=f"(v.y) : "r"(a) : "memory");
    return v;
}
__device__ __forceinline__ uint2 lds64(uint32_t a) {
    uint2 v;
    asm volatile("ld.shared.v2.u32 {%0,%1}, [%2];" : "=r"(v.x), "=r"(v.y) : "r"(a) : "memory");
    return v;
}
__device__ __forceinline__ uint32_t lds32(uint32_t a) {
    uint32_t v;
    asm volatile("ld.shared.u32 %0, [%1];" : "=r"(v) : "r"(a) : "memory");
    return v;
}
__device__ __forceinline__ float lds32f(uint32_t a) { return __uint_as_float(lds32(a)); }
__device__ __forceinline__ void sts128f(uint32_t a, float x, float y, float z, float w) {
    asm volatile("st.shared.v4.f32 [%0], {%1,%2,%3,%4};" ::"r"(a), "f"(x), "f"(y), "f"(z), "f"(w) : "memory");
}
__device__ __forceinline__ void sts32(uint32_t a, uint32_t v) {
    asm volatile("st.shared.u32 [%0], %1;" ::"r"(a), "r"(v) : "memory");
}
__device__ __forceinline__ void sts16(uint32_t a, unsigned short v) {
    asm volatile("st.shared.u16 [%0], %1;" ::"r"(a), "h"(v) : "memory");
}
__device__ __forceinline__ uint4 ldsm4t(uint32_t a) {
    uint4 v;
    asm volatile("ldmatrix.sync.aligned.m8n8.x4.trans.shared.b16 {%0,%1,%2,%3}, [%4];"
                 : "=r"(v.x), "=r"(v.y), "=r"(v.z), "=r"(v.w) : "r"(a) : "memory");
    return v;
}
__device__ __forceinline__ uint32_t pack_bf16(float lo, float hi) {
    uint32_t r;
    asm("cvt.rn.bf16x2.f32 %0, %1, %2;" : "=r"(r) : "f"(hi), "f"(lo));
    return r;
}
__device__ __forceinline__ float round_bf16(float v) { return __uint_as_float(pack_bf16(0.f, v) & 0xFFFF0000u); }
__device__ __forceinline__ float exp_score(float d) {
    float y;
    asm("ex2.approx.ftz.f32 %0, %1;" : "=f"(y) : "f"(d * (0.0625f * 1.4426950408889634f)));
    return y;
}
__device__ __forceinline__ uint32_t fu(float v) { return __float_as_uint(v); }

__device__ __forceinline__ float acc_value(unsigned long long tot) {
    return fmaf((float)(int)(uint32_t)(tot >> 32), 0x1p-24f, (float)((uint32_t)tot >> 10) * 0x1p-46f);
}
__device__ __noinline__ void finish_with_side(unsigned long long tot, unsigned long long* acc_p, __nv_bfloat16* out_p) {
    if ((tot & 31ull) != 16ull) return;
    __threadfence();
    const float side = atomicExch(&g_side[acc_p - g_acc], 0.0f);
    *out_p = __float2bfloat16(acc_value(tot) + side);
    *acc_p = 0ull;
}
__device__ __noinline__ void accumulate_slow(float sum, unsigned long long* acc_p, __nv_bfloat16* out_p) {
    atomicAdd(&g_side[acc_p - g_acc], sum);
    __threadfence();
    finish_with_side(atomicAdd(acc_p, 33ull) + 33ull, acc_p, out_p);
}

__global__ void __launch_bounds__(NTHREADS, 2)
decode_kernel(const __nv_bfloat16* __restrict__ x, const __nv_bfloat16* __restrict__ kc,
              const __nv_bfloat16* __restrict__ wq, __nv_bfloat16* __restrict__ out,
              unsigned long long* __restrict__ acc, const uint32_t zero,
              const __grid_constant__ CUtensorMap wq_map, const __grid_constant__ CUtensorMap wo_map,
              const __grid_constant__ CUtensorMap v_map) {
    asm volatile("prefetch.global.L2 [%0];" ::"l"((const char*)wq + (blockIdx.x * 224 + min(threadIdx.x, 223u)) * 128));

    extern __shared__ __align__(1024) unsigned char smem[];
    const uint32_t sb = (uint32_t)__cvta_generic_to_shared(smem);
    const int warp = threadIdx.x >> 5, lane = threadIdx.x & 31;
    const int cta = blockIdx.x;
    const int gk = cta >> 4, r = cta & 15, b = r >> 2, s = r & 3;
    const bool proj = r < 14;
    const int c = r - 7 * (r >= 7);
    const uint32_t qfull = sb + OFF_BAR, kfull = qfull + 8, vfull = kfull + 64, ofull = vfull + 128, empty = ofull + 32;
    const uint32_t qbar = empty + 14 * 8, stbar = qbar + 8, obar = qbar + 16, hbar = qbar + 24, done = qbar + 56;
    uint32_t spins = 0;

    if (warp == 0) {
        const bool leader = elect_one();
        if (leader) {
            mbar_init(qfull, 1);
            mbar_expect_tx(qfull, 28672 + 3584);
            tma2d(sb, &wq_map, (cta >> 1) * 64, (cta & 1) * 224, qfull);
            fence_mbar_init();
        }
        uint32_t due = now_ns() + T_K0 - (gk == 7 ? T_LEAD : 0);
        __syncwarp();
        cluster_arrive();
        cluster_wait();
        if (leader) {
            if (proj) bulk_g2s_mc(sb + OFF_OB + r * 256, (const char*)x + r * 256, 256, qfull, (uint16_t)0xFFFF);
            int row = (b * 8 + gk) * SK + WIN0 + s * 256;
            const char* kp = (const char*)kc + (size_t)row * 512;
            uint32_t bar = kfull, dst = sb + 2 * SLOT;
#pragma unroll 1
            for (int i = 0; i < 8; i++) {
                mbar_expect_tx(bar, 16384);
                if (i >= 4) mbar_wait(empty + 8 * (i - 4));
                pace(due, i < MIN_K ? qfull : bar - 8 * MIN_K);
                bulk_g2s(dst, kp, 16384, bar);
                if (i == 1) {
                    asm volatile("prefetch.tensormap [%0];" ::"l"(&v_map) : "memory");
                    asm volatile("prefetch.tensormap [%0];" ::"l"(&wo_map) : "memory");
                }
                due += T_K;
                kp += 16384;
                bar += 8;
                dst = (i == 3) ? sb : dst + SLOT;
            }
#pragma unroll 1
            for (int k = 0; k < 16; k++) {
                mbar_expect_tx(bar, 8192);
                mbar_wait(empty + 8 * (4 + (k >> 1)));
                const int d = k - MIN_V;
                pace(due, vfull + 8 * (d < 0 ? (d >> 1) : d));
                tma3d(dst, &v_map, row, bar);
                due += k < 12 ? T_V : T_V2;
                row += 16;
                bar += 8;
                dst = (k == 3) ? sb : dst + 8192;
            }
            if (proj) {
                due += T_GAP;
                mbar_wait(empty + 8 * 12);
                mbar_wait(empty + 8 * 13);
#pragma unroll 1
                for (int n = 0; n < 4; n++) {
                    mbar_expect_tx(bar, 8192);
                    if (gk != 7) mbar_wait(bar - 8 * MAX_O);
                    pace(due, bar - 8);
                    tma4d(sb + n * 8192, &wo_map, c * 64, (n + c) & 3, (2 * gk + (r >= 7)) * 2, bar);
                    due += T_O;
                    bar += 8;
                }
            }
            mbar_wait(done);
            if (spins >= SPIN_LIMIT) __trap();
        }
        return;
    }

    const int w = warp - 1, j = threadIdx.x - 32;
    const int g = lane >> 2, t = lane & 3;

    if (w < 7) {
        cluster_arrive();
        cluster_wait();
        const uint32_t qa = sb + (w * 32 + (lane >> 4) * 8 + (lane & 7)) * 128;
        const uint32_t xa = sb + OFF_OB + (g & 3) * 896 + (cta & 1) * 448 + w * 64 + t * 4;
        mbar_wait(qfull);
        const uint32_t x0 = lds32(xa), x1 = lds32(xa + 16), x2 = lds32(xa + 32), x3 = lds32(xa + 48);
        float cq[4][4];
#pragma unroll
        for (int m = 0; m < 4; m++) {
            const uint32_t a = qa + (((2 * m + ((lane >> 3) & 1)) ^ (lane & 7)) << 4);
            const uint4 f0 = ldsm4t(a), f1 = ldsm4t(a + 2048);
            cq[m][0] = cq[m][1] = cq[m][2] = cq[m][3] = 0.f;
            mma16816(cq[m], f0, x0, x1);
            mma16816(cq[m], f1, x2, x3);
        }
        slot_release(empty + 8 * (w >> 2), fu(cq[0][0]) ^ fu(cq[1][0]) ^ fu(cq[2][0]) ^ fu(cq[3][0]), zero, lane);
        const int hf = t >> 1;
        const uint32_t qr = sb + OFF_QRED + w * 1024 + (t & 1) * 512 + hf * 128 + g * 16;
        sts128f(qr, hf ? cq[0][2] : cq[0][0], hf ? cq[1][2] : cq[1][0], hf ? cq[2][2] : cq[2][0], hf ? cq[3][2] : cq[3][0]);
        sts128f(qr + 256, hf ? cq[0][3] : cq[0][1], hf ? cq[1][3] : cq[1][1], hf ? cq[2][3] : cq[2][1], hf ? cq[3][3] : cq[3][1]);
    } else {
        if (lane == 0) {
#pragma unroll
            for (int i = 0; i < 28; i++) mbar_init(kfull + 8 * i, 1);
#pragma unroll
            for (int i = 0; i < 14; i++) mbar_init(empty + 8 * i, i == 1 ? 3 : (i < 10 ? 4 : 8));
#pragma unroll
            for (int i = 0; i < 7; i++) mbar_init(qbar + 8 * i, 1);
            mbar_init(done, 8);
            mbar_expect_tx(qbar, 4096);
            mbar_expect_tx(stbar, 64);
            mbar_expect_tx(obar, 2048);
#pragma unroll
            for (int i = 0; i < 4; i++) mbar_expect_tx(hbar + 8 * i, 512);
            fence_mbar_init();
        }
        __syncwarp();
        cluster_arrive();
        cluster_wait();
    }
    bar_compute();
    {
        const int pk = j >> 2;
        const uint32_t ra = sb + OFF_QRED + pk * 16;
        float4 a = lds128f(ra);
#pragma unroll
        for (int ww = 1; ww < 7; ww++) {
            const float4 v = lds128f(ra + ww * 1024);
            a.x += v.x; a.y += v.y; a.z += v.z; a.w += v.w;
        }
        const uint32_t dst = (pk >> 4) * 4 + (j & 3);
        st_async128(mapa(sb + OFF_QBUF + (r & 1) * 2048 + (r >> 1) * 256 + (pk & 15) * 16, dst),
                    fu(a.x), fu(a.y), fu(a.z), fu(a.w), mapa(qbar, dst));
        mbar_wait(qbar);
        const uint32_t qb = sb + OFF_QBUF + (j >> 5) * 256 + (j & 7) * 32 + ((j >> 3) & 3) * 4;
        const float q0 = lds32f(qb) + lds32f(qb + 2048), q1 = lds32f(qb + 16) + lds32f(qb + 2064);
        sts32(sb + OFF_QS + ((j >> 5) & 3) * 256 + (j & 1) * 128 + (j >> 7) * 64 + ((j >> 2) & 3) * 16 + ((j >> 4) & 1) * 8 + ((j >> 1) & 1) * 4,
              pack_bf16(q0, q1));
    }
    bar_compute();

    float s0 = 0.f, s1 = 0.f;
    {
        uint2 qf[8];
        const uint32_t qa = sb + OFF_QS + (g >> 2) * 128 + (g & 1) * 64 + t * 16;
        const uint32_t qx = ((g >> 1) & 1) * 8;
#pragma unroll
        for (int i = 0; i < 8; i++) qf[i] = lds64(qa + (i >> 1) * 256 + (((i & 1) * 8) ^ qx));
        const uint32_t kx = (g & 1) * 64;
        const uint32_t krow = sb + ((w & 3) * 8 + g) * 512 + t * 16;
        const int src = (lane & 28) + (g & 1);
#pragma unroll 1
        for (int k = 0; k < 4; k++) {
            const int ch = 2 * k + (w >> 2);
            const uint32_t ka = krow + (ch >= 4 ? ch - 4 : ch + 2) * SLOT;
            mbar_wait(kfull + 8 * ch);
            float a0[4] = {0.f, 0.f, 0.f, 0.f}, a1[4] = {0.f, 0.f, 0.f, 0.f};
#pragma unroll
            for (int i = 0; i < 8; i += 2) {
                const uint4 r0 = lds128(ka + ((i * 64) ^ kx)), r1 = lds128(ka + (((i + 1) * 64) ^ kx));
                mma16816(a0, r0, qf[i].x, qf[i].y);
                mma16816(a1, r1, qf[i + 1].x, qf[i + 1].y);
            }
            const float e0 = __shfl_sync(0xffffffffu, a0[0] + a1[0], src) + __shfl_sync(0xffffffffu, a0[2] + a1[2], src + 2);
            const float e1 = __shfl_sync(0xffffffffu, a0[1] + a1[1], src) + __shfl_sync(0xffffffffu, a0[3] + a1[3], src + 2);
            slot_release(empty + 8 * (2 + ch), fu(e0), zero, lane);
            if (t == k) { s0 = e0; s1 = e1; }
        }
    }
    float Mown;
    {
        s0 = round_bf16(s0);
        s1 = round_bf16(s1);
        float m0 = s0, m1 = s1;
#pragma unroll
        for (int o = 16; o > 0; o >>= 1) {
            m0 = fmaxf(m0, __shfl_xor_sync(0xffffffffu, m0, o));
            m1 = fmaxf(m1, __shfl_xor_sync(0xffffffffu, m1, o));
        }
        if (lane < 2) sts32(sb + OFF_WST + (w * 2 + lane) * 4, fu(lane ? m1 : m0));
        bar_compute();
        const float4 u0 = lds128f(sb + OFF_WST), u1 = lds128f(sb + OFF_WST + 16), u2 = lds128f(sb + OFF_WST + 32), u3 = lds128f(sb + OFF_WST + 48);
        const float M0 = fmaxf(fmaxf(fmaxf(u0.x, u0.z), fmaxf(u1.x, u1.z)), fmaxf(fmaxf(u2.x, u2.z), fmaxf(u3.x, u3.z)));
        const float M1 = fmaxf(fmaxf(fmaxf(u0.y, u0.w), fmaxf(u1.y, u1.w)), fmaxf(fmaxf(u2.y, u2.w), fmaxf(u3.y, u3.w)));
        Mown = (t & 1) ? M1 : M0;
        const uint32_t p = pack_bf16(exp_score(s0 - M0), exp_score(s1 - M1));
        const uint32_t pa = sb + OFF_PS + (4 * t + (w >> 1)) * 64 + (g >> 1) * 8 + (w & 1) * 4 + (g & 1) * 2;
        sts16(pa, (unsigned short)(p & 0xFFFFu));
        sts16(pa + 32, (unsigned short)(p >> 16));
        float l0 = __uint_as_float(p << 16), l1 = __uint_as_float(p & 0xFFFF0000u);
#pragma unroll
        for (int o = 16; o > 0; o >>= 1) {
            l0 += __shfl_xor_sync(0xffffffffu, l0, o);
            l1 += __shfl_xor_sync(0xffffffffu, l1, o);
        }
        if (lane < 2) sts32(sb + OFF_WST + 64 + (w * 2 + lane) * 4, fu(lane ? l1 : l0));
        bar_compute();
        if (j < 4) {
            const float4 v0 = lds128f(sb + OFF_WST + 64), v1 = lds128f(sb + OFF_WST + 80), v2 = lds128f(sb + OFF_WST + 96), v3 = lds128f(sb + OFF_WST + 112);
            const float L0 = ((v0.x + v0.z) + (v1.x + v1.z)) + ((v2.x + v2.z) + (v3.x + v3.z));
            const float L1 = ((v0.y + v0.w) + (v1.y + v1.w)) + ((v2.y + v2.w) + (v3.y + v3.w));
            st_async128(mapa(sb + OFF_WST + 128 + s * 16, b * 4 + j), fu(M0), fu(L0), fu(M1), fu(L1), mapa(stbar, b * 4 + j));
        }
    }

    const uint32_t h1_dst = pin(mapa(sb + OFF_HOP + r * 128 + (t >> 1) * 64 + g * 8, (t & 1) * 8 + w));
    const uint32_t h1_bar = pin(mapa(hbar + 8 * b, (t & 1) * 8 + w));
    const uint32_t h2_grp = (w >> 2) * 4 + (lane >> 3);
    const uint32_t h2_rank = h2_grp < 7 ? (r >> 3) * 7 + h2_grp : 14 + (r >> 3);
    const uint32_t h2_dst = pin(mapa(sb + OFF_OB + (w & 3) * OB_STRIDE + ((r - h2_grp) & 3) * 128 + ((r >> 2) & 1) * 64 +
                                     (lane & 3) * 16 + ((lane >> 2) & 1) * 8, h2_rank));
    const uint32_t h2_bar = pin(mapa(obar, h2_rank));
    const uint32_t h2_src = pin(sb + OFF_HOP + (w & 3) * 512 + (lane & 7) * 16);
    const uint32_t h2_wait = pin(hbar + 8 * (w & 3));
    const uint32_t bars = pin(obar);
    const uint32_t wo_src = pin(sb + (((lane >> 3) & 1) * 16 + (lane >> 4) * 8 + (lane & 7)) * 128 + ((w ^ (lane & 7)) << 4));
    const uint32_t ob_src = pin(sb + OFF_OB + (g & 3) * OB_STRIDE + (g >> 2) * 64 + t * 16);
    unsigned long long* acc_p = pin_ptr(acc + (c * 16 + (j >> 4)) * 32 + (j & 15));
    __nv_bfloat16* out_p = pin_ptr(out + (g & 3) * 448 + c * 64 + w * 8 + 2 * t + (g >> 2));
    const uint32_t k_one = pin(zero + 1u);
    const bool t_hi = pin(t >> 1) != 0, g_hi = pin(g >> 2) != 0, proj_on = pin(proj ? 1u : 0u) != 0;

    float acc0[4] = {0.f, 0.f, 0.f, 0.f}, acc1[4] = {0.f, 0.f, 0.f, 0.f};
    float wgt;
    {
        const uint32_t va0 = pin(sb + (w >> 1) * 2048 + ((lane >> 4) * 8 + (lane & 7)) * 128 + ((((w & 1) * 4 + ((lane >> 3) & 1)) ^ (lane & 7)) << 4));
        const uint32_t va1 = pin(va0 ^ 32);
        const uint32_t pa = pin(sb + OFF_PS + ((g >> 1) & 1) * 32 + t * 8);
        const uint32_t vb = bars - (obar - vfull);
#pragma unroll 1
        for (int k = 0; k < 8; k += 2) {
            const uint32_t so = (k < 4 ? k + 8 : k - 4) * 8192;
            const uint2 p0 = lds64(pa + k * 64), p1 = lds64(pa + k * 64 + 64);
            mbar_wait(vb + 8 * k);
            const uint4 f0 = ldsm4t(va0 + so), f1 = ldsm4t(va1 + so);
            mma16816(acc0, f0, p0.x, p0.y);
            mma16816(acc1, f1, p0.x, p0.y);
            mbar_wait(vb + 8 * k + 8);
            const uint4 f2 = ldsm4t(va0 + so + 8192), f3 = ldsm4t(va1 + so + 8192);
            mma16816(acc0, f2, p1.x, p1.y);
            mma16816(acc1, f3, p1.x, p1.y);
            slot_release(empty + 8 * (10 + (k >> 1)), fu(acc0[0]) ^ fu(acc1[0]), zero, lane);
        }
        uint2 pw[8];
#pragma unroll
        for (int k = 8; k < 16; k++) pw[k - 8] = lds64(pa + k * 64);
        {
            mbar_wait(stbar);
            const uint32_t sa = sb + OFF_WST + 128 + (t & 1) * 8;
            const float2 z0 = lds64f(sa), z1 = lds64f(sa + 16), z2 = lds64f(sa + 32), z3 = lds64f(sa + 48);
            const float mx = fmaxf(fmaxf(z0.x, z1.x), fmaxf(z2.x, z3.x));
            const float W = (exp_score(z0.x - mx) * z0.y + exp_score(z1.x - mx) * z1.y) +
                            (exp_score(z2.x - mx) * z2.y + exp_score(z3.x - mx) * z3.y);
            wgt = __uint_as_float(pin(fu(__fdividef(exp_score(Mown - mx), W))));
        }
        uint4 f0, f1;
#pragma unroll
        for (int k = 8; k < 16; k++) {
            mbar_wait_fast(vb + 8 * k);
            const uint4 n0 = ldsm4t(va0 + (k - 4) * 8192), n1 = ldsm4t(va1 + (k - 4) * 8192);
            if (k > 8) {
                mma16816(acc0, f0, pw[k - 9].x, pw[k - 9].y);
                mma16816(acc1, f1, pw[k - 9].x, pw[k - 9].y);
            }
            f0 = n0; f1 = n1;
        }
        mma16816(acc0, f0, pw[7].x, pw[7].y);
        mma16816(acc1, f1, pw[7].x, pw[7].y);
    }
    st_async64(h1_dst, fu((t_hi ? acc1[0] : acc0[0]) * wgt), fu((t_hi ? acc1[2] : acc0[2]) * wgt), h1_bar);
    {
        mbar_wait_fast(h2_wait);
        const float4 v0 = lds128f(h2_src), v1 = lds128f(h2_src + 128), v2 = lds128f(h2_src + 256), v3 = lds128f(h2_src + 384);
        st_async64(h2_dst, pack_bf16((v0.x + v1.x) + (v2.x + v3.x), (v0.z + v1.z) + (v2.z + v3.z)),
                   pack_bf16((v0.y + v1.y) + (v2.y + v3.y), (v0.w + v1.w) + (v2.w + v3.w)), h2_bar);
    }
    if (!proj_on) {
        mbar_wait_fast(bars);
        slot_release(bars + (done - obar), 0u, 0u, lane);
        return;
    }
    float sum;
    {
        const uint32_t ob = bars - (obar - ofull);
        float x0[4] = {0.f, 0.f, 0.f, 0.f}, x1[4] = {0.f, 0.f, 0.f, 0.f}, y0[4] = {0.f, 0.f, 0.f, 0.f}, y1[4] = {0.f, 0.f, 0.f, 0.f};
        uint4 bp[4], bq[4], oa[4];
#pragma unroll
        for (int n = 0; n < 3; n++) {
            mbar_wait_fast(ob + 8 * n);
            bp[n] = ldsm4t(wo_src + n * 8192);
            bq[n] = ldsm4t(wo_src + n * 8192 + 4096);
        }
        mbar_wait_fast(bars);
#pragma unroll
        for (int n = 0; n < 4; n++) oa[n] = lds128(ob_src + n * 128);
#pragma unroll
        for (int n = 0; n < 4; n++) {
            if (n == 3) {
                mbar_wait_fast(ob + 24);
                bp[3] = ldsm4t(wo_src + 3 * 8192);
                bq[3] = ldsm4t(wo_src + 3 * 8192 + 4096);
            }
            mma16816(x0, oa[n], bp[n].x, bp[n].y);
            mma16816(y0, oa[n], bp[n].z, bp[n].w);
            mma16816(x1, oa[n], bq[n].x, bq[n].y);
            mma16816(y1, oa[n], bq[n].z, bq[n].w);
        }
        float keep = x0[0] + y0[2], send = x0[1] + y0[3];
        if (g_hi) { send = x1[0] + y1[2]; keep = x1[1] + y1[3]; }
        sum = keep + __shfl_xor_sync(0xffffffffu, send, 16);
    }
    const uint32_t bits = fu(sum);
    const uint32_t sh = 129u - ((bits >> 23) & 0xFFu);
    const uint32_t smant = (((bits << 3) & 0x3FFFFF8u) | 0x4000000u) ^ (uint32_t)((int)bits >> 31);
    long long fx;
    asm("shr.s64 %0, %1, %2;" : "=l"(fx) : "l"((long long)((unsigned long long)smant << 32)), "r"(sh));
    const unsigned long long inc = ((unsigned long long)fx & 0xFFFFFFFF00000000ull) | (((uint32_t)fx & ~0x3FFu) | k_one);
    const bool fast = __any_sync(0xffffffffu, fabsf(sum) >= 0x1p-22f) && fabsf(sum) < 8.0f;
    unsigned long long tot = 0ull;
    asm volatile("{\n.reg .pred p;\nsetp.ne.u32 p, %3, 0;\n@p atom.relaxed.gpu.global.add.u64 %0, [%1], %2;\n}"
                 : "+l"(tot) : "l"(acc_p), "l"(inc), "r"((uint32_t)fast) : "memory");
    slot_release(bars + (done - obar), 0u, 0u, lane);
    if (!fast) { accumulate_slow(sum, acc_p, out_p); return; }
    tot += inc;
    const uint32_t cnt = (uint32_t)tot & 0x3FFu;
    asm volatile("{\n.reg .pred p;\nsetp.eq.u32 p, %3, 16;\n@p st.global.u16 [%0], %1;\n@p st.global.u64 [%2], 0;\n}"
                 ::"l"(out_p), "h"(__bfloat16_as_ushort(__float2bfloat16(acc_value(tot)))), "l"(acc_p), "r"(cnt) : "memory");
    if (cnt > 16u) finish_with_side(tot, acc_p, out_p);
}

typedef CUresult (*EncodeFn)(CUtensorMap*, CUtensorMapDataType, cuuint32_t, void*, const cuuint64_t*, const cuuint64_t*,
                             const cuuint32_t*, const cuuint32_t*, CUtensorMapInterleave, CUtensorMapSwizzle,
                             CUtensorMapL2promotion, CUtensorMapFloatOOBfill);

}

extern "C" void kernel_launch(void* const* d_in, const int* in_sizes, int n_in, void* d_out, int out_size) {
    (void)in_sizes; (void)n_in; (void)out_size;
    static EncodeFn encode = nullptr;
    static void* acc = nullptr;
    if (!encode) {
        cudaDriverEntryPointQueryResult qr;
        cudaGetDriverEntryPoint("cuTensorMapEncodeTiled", (void**)&encode, cudaEnableDefault, &qr);
        cudaGetSymbolAddress(&acc, g_acc);
        cudaFuncSetAttribute(decode_kernel, cudaFuncAttributeMaxDynamicSharedMemorySize, SMEM_BYTES);
        cudaFuncSetAttribute(decode_kernel, cudaFuncAttributeNonPortableClusterSizeAllowed, 1);
    }
    const cuuint32_t estr[4] = {1, 1, 1, 1};
    CUtensorMap wq_map, wo_map, v_map;
    {
        const cuuint64_t dim[2] = {4096, 448}, str[1] = {8192};
        const cuuint32_t box[2] = {64, 224};
        encode(&wq_map, CU_TENSOR_MAP_DATA_TYPE_BFLOAT16, 2, d_in[3], dim, str, box, estr, CU_TENSOR_MAP_INTERLEAVE_NONE,
               CU_TENSOR_MAP_SWIZZLE_128B, CU_TENSOR_MAP_L2_PROMOTION_NONE, CU_TENSOR_MAP_FLOAT_OOB_FILL_NONE);
    }
    {
        const cuuint64_t dim[4] = {448, 32, 4, 32}, str[3] = {896, 896 * 32, 896 * 128};
        const cuuint32_t box[4] = {64, 32, 1, 2};
        encode(&wo_map, CU_TENSOR_MAP_DATA_TYPE_BFLOAT16, 4, d_in[4], dim, str, box, estr, CU_TENSOR_MAP_INTERLEAVE_NONE,
               CU_TENSOR_MAP_SWIZZLE_128B, CU_TENSOR_MAP_L2_PROMOTION_NONE, CU_TENSOR_MAP_FLOAT_OOB_FILL_NONE);
    }
    {
        const cuuint64_t dim[3] = {64, 4ull * 8 * SK, 4}, str[2] = {512, 128};
        const cuuint32_t box[3] = {64, 16, 4};
        encode(&v_map, CU_TENSOR_MAP_DATA_TYPE_BFLOAT16, 3, d_in[2], dim, str, box, estr, CU_TENSOR_MAP_INTERLEAVE_NONE,
               CU_TENSOR_MAP_SWIZZLE_128B, CU_TENSOR_MAP_L2_PROMOTION_NONE, CU_TENSOR_MAP_FLOAT_OOB_FILL_NONE);
    }
    cudaLaunchConfig_t cfg = {};
    cfg.gridDim = dim3(128);
    cfg.blockDim = dim3(NTHREADS);
    cfg.dynamicSmemBytes = SMEM_BYTES;
    cfg.stream = cudaStreamPerThread;
    cudaLaunchAttribute attr[2];
    attr[0].id = cudaLaunchAttributeClusterDimension;
    attr[0].val.clusterDim.x = 16; attr[0].val.clusterDim.y = 1; attr[0].val.clusterDim.z = 1;
    attr[1].id = cudaLaunchAttributeClusterSchedulingPolicyPreference;
    attr[1].val.clusterSchedulingPolicyPreference = cudaClusterSchedulingPolicyLoadBalancing;
    cfg.attrs = attr;
    cfg.numAttrs = 2;
    cudaLaunchKernelEx(&cfg, decode_kernel, (const __nv_bfloat16*)d_in[0], (const __nv_bfloat16*)d_in[1],
                       (const __nv_bfloat16*)d_in[3], (__nv_bfloat16*)d_out, (unsigned long long*)acc, 0u,
                       wq_map, wo_map, v_map);
}
```

```cpp
#include <cuda_runtime.h>
#include <cuda_bf16.h>
#include <cuda.h>
#include <stdint.h>

namespace {

constexpr int SK = 4096, WIN0 = 3072;
constexpr int SLOT = 16384;
constexpr int OFF_BAR  = 6 * SLOT;
constexpr int OFF_QBUF = OFF_BAR + 416;
constexpr int OFF_QS   = OFF_QBUF + 4096;
constexpr int OFF_WST  = OFF_QS + 1024;
constexpr int OB_STRIDE = 576;
constexpr int OFF_OB   = OFF_WST + 192;
constexpr int OFF_HOP  = OFF_OB + 4 * OB_STRIDE;
constexpr int OFF_QRED = OFF_HOP + 2048;
constexpr int OFF_PS   = OFF_QRED;
constexpr int SMEM_BYTES = OFF_QRED + 7 * 1024;
static_assert(SMEM_BYTES <= 115712, "two CTAs must fit on one SM");
constexpr int NTHREADS = 288;
constexpr int SPIN_LIMIT = 1 << 20;

constexpr int T_K0   = 300;
constexpr int T_K    = 670;
constexpr int T_V    = 345;
constexpr int T_V2   = 300;
constexpr int T_GAP  = 30;
constexpr int T_O    = 300;
constexpr int T_LEAD = 1600;
constexpr int MIN_K = 2, MIN_V = 4;
constexpr int MAX_O = 6;

constexpr int ACC_WORDS = 1792 * 2;
__device__ __align__(1024) unsigned long long g_acc[ACC_WORDS];
__device__ float g_side[ACC_WORDS];

__device__ __forceinline__ void mbar_init(uint32_t bar, uint32_t cnt) {
    asm volatile("mbarrier.init.shared::cta.b64 [%0], %1;" ::"r"(bar), "r"(cnt) : "memory");
}
__device__ __forceinline__ void mbar_expect_tx(uint32_t bar, uint32_t bytes) {
    asm volatile("mbarrier.arrive.expect_tx.shared::cta.b64 _, [%0], %1;" ::"r"(bar), "r"(bytes) : "memory");
}
__device__ __forceinline__ void slot_release(uint32_t bar, uint32_t dep, uint32_t zero, int lane) {
    if (lane == 0) asm volatile("mbarrier.arrive.shared::cta.b64 _, [%0];" ::"r"(bar + (dep & zero)) : "memory");
}
__device__ __forceinline__ void mbar_wait_n(uint32_t bar, uint32_t& n) {
    asm volatile("{\n.reg .pred p, q;\n"
                 "WAIT_LOOP:\n"
                 "mbarrier.try_wait.parity.shared::cta.b64 p, [%1], 0;\n"
                 "add.u32 %0, %0, 1;\n"
                 "setp.lt.and.u32 q, %0, %2, !p;\n"
                 "@q bra.uni WAIT_LOOP;\n}"
                 : "+r"(n) : "r"(bar), "n"(SPIN_LIMIT) : "memory");
}
#define mbar_wait(bar) mbar_wait_n(bar, spins)
__device__ __forceinline__ void mbar_wait_fast(uint32_t bar) {
    asm volatile("{\n.reg .pred p;\nWAIT_LOOP:\nmbarrier.try_wait.parity.shared::cta.b64 p, [%0], 0;\n@!p bra.uni WAIT_LOOP;\n}"
                 ::"r"(bar) : "memory");
}
__device__ __forceinline__ uint32_t now_ns() {
    uint32_t t;
    asm volatile("mov.u32 %0, %%globaltimer_lo;" : "=r"(t)::"memory");
    return t;
}
__device__ __forceinline__ void pace(uint32_t due, uint32_t bar) {
    while ((int)(now_ns() - due) < 0) {
        uint32_t ok;
        asm volatile("{\n.reg .pred p;\nmbarrier.test_wait.parity.shared::cta.b64 p, [%1], 0;\nselp.u32 %0, 1, 0, p;\n}"
                     : "=r"(ok) : "r"(bar) : "memory");
        if (ok) break;
    }
}
__device__ __forceinline__ void bulk_g2s(uint32_t dst, const void* src, uint32_t bytes, uint32_t bar) {
    asm volatile("cp.async.bulk.shared::cluster.global.mbarrier::complete_tx::bytes [%0], [%1], %2, [%3];"
                 ::"r"(dst), "l"(src), "r"(bytes), "r"(bar) : "memory");
}
__device__ __forceinline__ void bulk_g2s_mc(uint32_t dst, const void* src, uint32_t bytes, uint32_t bar, uint16_t mask) {
    asm volatile("cp.async.bulk.shared::cluster.global.mbarrier::complete_tx::bytes.multicast::cluster [%0], [%1], %2, [%3], %4;"
                 ::"r"(dst), "l"(src), "r"(bytes), "r"(bar), "h"(mask) : "memory");
}
__device__ __forceinline__ void tma2d(uint32_t dst, const CUtensorMap* tm, int c0, int c1, uint32_t bar) {
    asm volatile("cp.async.bulk.tensor.2d.shared::cluster.global.mbarrier::complete_tx::bytes [%0], [%1, {%3, %4}], [%2];"
                 ::"r"(dst), "l"(tm), "r"(bar), "r"(c0), "r"(c1) : "memory");
}
__device__ __forceinline__ void tma3d(uint32_t dst, const CUtensorMap* tm, int c1, uint32_t bar) {
    asm volatile("cp.async.bulk.tensor.3d.shared::cluster.global.mbarrier::complete_tx::bytes [%0], [%1, {%3, %4, %3}], [%2];"
                 ::"r"(dst), "l"(tm), "r"(bar), "r"(0), "r"(c1) : "memory");
}
__device__ __forceinline__ void tma4d(uint32_t dst, const CUtensorMap* tm, int c0, int c2, int c3, uint32_t bar) {
    asm volatile("cp.async.bulk.tensor.4d.shared::cluster.global.mbarrier::complete_tx::bytes [%0], [%1, {%3, %4, %5, %6}], [%2];"
                 ::"r"(dst), "l"(tm), "r"(bar), "r"(c0), "r"(0), "r"(c2), "r"(c3) : "memory");
}
__device__ __forceinline__ uint32_t pin(uint32_t v) {
    uint32_t o;
    asm volatile("shfl.sync.bfly.b32 %0, %1, 0, 0x1f, 0xffffffff;" : "=r"(o) : "r"(v));
    return o;
}
template <typename T> __device__ __forceinline__ T* pin_ptr(T* p) {
    const unsigned long long a = (unsigned long long)p;
    return (T*)(((unsigned long long)pin((uint32_t)(a >> 32)) << 32) | pin((uint32_t)a));
}
__device__ __forceinline__ bool elect_one() {
    uint32_t p;
    asm volatile("{\n.reg .pred P;\nelect.sync _|P, 0xffffffff;\nselp.u32 %0, 1, 0, P;\n}" : "=r"(p));
    return p != 0;
}
__device__ __forceinline__ void bar_compute() { asm volatile("bar.sync 1, 256;" ::: "memory"); }
__device__ __forceinline__ void cluster_arrive() { asm volatile("barrier.cluster.arrive.relaxed.aligned;" ::: "memory"); }
__device__ __forceinline__ void cluster_wait() { asm volatile("barrier.cluster.wait.aligned;" ::: "memory"); }
__device__ __forceinline__ void fence_mbar_init() { asm volatile("fence.mbarrier_init.release.cluster;" ::: "memory"); }
__device__ __forceinline__ uint32_t mapa(uint32_t a, uint32_t rank) {
    uint32_t o;
    asm("mapa.shared::cluster.u32 %0, %1, %2;" : "=r"(o) : "r"(a), "r"(rank));
    return o;
}
__device__ __forceinline__ void st_async128(uint32_t a, uint32_t x, uint32_t y, uint32_t z, uint32_t w, uint32_t bar) {
    asm volatile("st.async.shared::cluster.mbarrier::complete_tx::bytes.v4.b32 [%0], {%1,%2,%3,%4}, [%5];"
                 ::"r"(a), "r"(x), "r"(y), "r"(z), "r"(w), "r"(bar) : "memory");
}
__device__ __forceinline__ void st_async64(uint32_t a, uint32_t x, uint32_t y, uint32_t bar) {
    asm volatile("st.async.shared::cluster.mbarrier::complete_tx::bytes.v2.b32 [%0], {%1,%2}, [%3];"
                 ::"r"(a), "r"(x), "r"(y), "r"(bar) : "memory");
}
__device__ __forceinline__ void mma16816(float (&c)[4], const uint4& a, uint32_t b0, uint32_t b1) {
    asm volatile("mma.sync.aligned.m16n8k16.row.col.f32.bf16.bf16.f32 {%0,%1,%2,%3}, {%4,%5,%6,%7}, {%8,%9}, {%0,%1,%2,%3};"
                 : "+f"(c[0]), "+f"(c[1]), "+f"(c[2]), "+f"(c[3])
                 : "r"(a.x), "r"(a.y), "r"(a.z), "r"(a.w), "r"(b0), "r"(b1));
}
__device__ __forceinline__ uint4 lds128(uint32_t a) {
    uint4 v;
    asm volatile("ld.shared.v4.u32 {%0,%1,%2,%3}, [%4];" : "=r"(v.x), "=r"(v.y), "=r"(v.z), "=r"(v.w) : "r"(a) : "memory");
    return v;
}
__device__ __forceinline__ float4 lds128f(uint32_t a) {
    float4 v;
    asm volatile("ld.shared.v4.f32 {%0,%1,%2,%3}, [%4];" : "=f"(v.x), "=f"(v.y), "=f"(v.z), "=f"(v.w) : "r"(a) : "memory");
    return v;
}
__device__ __forceinline__ float2 lds64f(uint32_t a) {
    float2 v;
    asm volatile("ld.shared.v2.f32 {%0,%1}, [%2];" : "=f"(v.x), "=f"(v.y) : "r"(a) : "memory");
    return v;
}
__device__ __forceinline__ uint2 lds64(uint32_t a) {
    uint2 v;
    asm volatile("ld.shared.v2.u32 {%0,%1}, [%2];" : "=r"(v.x), "=r"(v.y) : "r"(a) : "memory");
    return v;
}
__device__ __forceinline__ uint32_t lds32(uint32_t a) {
    uint32_t v;
    asm volatile("ld.shared.u32 %0, [%1];" : "=r"(v) : "r"(a) : "memory");
    return v;
}
__device__ __forceinline__ float lds32f(uint32_t a) { return __uint_as_float(lds32(a)); }
__device__ __forceinline__ void sts128f(uint32_t a, float x, float y, float z, float w) {
    asm volatile("st.shared.v4.f32 [%0], {%1,%2,%3,%4};" ::"r"(a), "f"(x), "f"(y), "f"(z), "f"(w) : "memory");
}
__device__ __forceinline__ void sts32(uint32_t a, uint32_t v) {
    asm volatile("st.shared.u32 [%0], %1;" ::"r"(a), "r"(v) : "memory");
}
__device__ __forceinline__ void sts16(uint32_t a, unsigned short v) {
    asm volatile("st.shared.u16 [%0], %1;" ::"r"(a), "h"(v) : "memory");
}
__device__ __forceinline__ uint4 ldsm4t(uint32_t a) {
    uint4 v;
    asm volatile("ldmatrix.sync.aligned.m8n8.x4.trans.shared.b16 {%0,%1,%2,%3}, [%4];"
                 : "=r"(v.x), "=r"(v.y), "=r"(v.z), "=r"(v.w) : "r"(a) : "memory");
    return v;
}
__device__ __forceinline__ uint32_t pack_bf16(float lo, float hi) {
    uint32_t r;
    asm("cvt.rn.bf16x2.f32 %0, %1, %2;" : "=r"(r) : "f"(hi), "f"(lo));
    return r;
}
__device__ __forceinline__ float round_bf16(float v) { return __uint_as_float(pack_bf16(0.f, v) & 0xFFFF0000u); }
__device__ __forceinline__ float exp_score(float d) {
    float y;
    asm("ex2.approx.ftz.f32 %0, %1;" : "=f"(y) : "f"(d * (0.0625f * 1.4426950408889634f)));
    return y;
}
__device__ __forceinline__ uint32_t fu(float v) { return __float_as_uint(v); }

__device__ __forceinline__ float acc_value(unsigned long long tot) {
    return fmaf((float)(int)(uint32_t)(tot >> 32), 0x1p-24f, (float)((uint32_t)tot >> 10) * 0x1p-46f);
}
__device__ __noinline__ void finish_with_side(unsigned long long tot, unsigned long long* acc_p, __nv_bfloat16* out_p) {
    if ((tot & 31ull) != 16ull) return;
    __threadfence();
    const float side = atomicExch(&g_side[acc_p - g_acc], 0.0f);
    *out_p = __float2bfloat16(acc_value(tot) + side);
    *acc_p = 0ull;
}
__device__ __noinline__ void accumulate_slow(float sum, unsigned long long* acc_p, __nv_bfloat16* out_p) {
    atomicAdd(&g_side[acc_p - g_acc], sum);
    __threadfence();
    finish_with_side(atomicAdd(acc_p, 33ull) + 33ull, acc_p, out_p);
}

__global__ void __launch_bounds__(NTHREADS, 2)
decode_kernel(const __nv_bfloat16* __restrict__ x, const __nv_bfloat16* __restrict__ kc,
              const __nv_bfloat16* __restrict__ wq, __nv_bfloat16* __restrict__ out,
              unsigned long long* __restrict__ acc, const uint32_t zero,
              const __grid_constant__ CUtensorMap wq_map, const __grid_constant__ CUtensorMap wo_map,
              const __grid_constant__ CUtensorMap v_map) {
    asm volatile("prefetch.global.L2 [%0];" ::"l"((const char*)wq + (blockIdx.x * 224 + min(threadIdx.x, 223u)) * 128));

    extern __shared__ __align__(1024) unsigned char smem[];
    const uint32_t sb = (uint32_t)__cvta_generic_to_shared(smem);
    const int warp = threadIdx.x >> 5, lane = threadIdx.x & 31;
    const int cta = blockIdx.x;
    const int gk = cta >> 4, r = cta & 15, b = r >> 2, s = r & 3;
    const bool proj = r < 14;
    const int c = r - 7 * (r >= 7);
    const uint32_t qfull = sb + OFF_BAR, kfull = qfull + 8, vfull = kfull + 64, ofull = vfull + 128, empty = ofull + 32;
    const uint32_t qbar = empty + 14 * 8, stbar = qbar + 8, obar = qbar + 16, hbar = qbar + 24, done = qbar + 56;
    uint32_t spins = 0;

    if (warp == 0) {
        const bool leader = elect_one();
        if (leader) {
            mbar_init(qfull, 1);
            mbar_expect_tx(qfull, 28672 + 3584);
            tma2d(sb, &wq_map, (cta >> 1) * 64, (cta & 1) * 224, qfull);
            fence_mbar_init();
        }
        uint32_t due = now_ns() + T_K0 - (gk == 7 ? T_LEAD : 0);
        __syncwarp();
        cluster_arrive();
        cluster_wait();
        if (leader) {
            if (proj) bulk_g2s_mc(sb + OFF_OB + r * 256, (const char*)x + r * 256, 256, qfull, (uint16_t)0xFFFF);
            int row = (b * 8 + gk) * SK + WIN0 + s * 256;
            const char* kp = (const char*)kc + (size_t)row * 512;
            uint32_t bar = kfull, dst = sb + 2 * SLOT;
#pragma unroll 1
            for (int i = 0; i < 8; i++) {
                mbar_expect_tx(bar, 16384);
                if (i >= 4) mbar_wait(empty + 8 * (i - 4));
                pace(due, i < MIN_K ? qfull : bar - 8 * MIN_K);
                bulk_g2s(dst, kp, 16384, bar);
                if (i == 1) {
                    asm volatile("prefetch.tensormap [%0];" ::"l"(&v_map) : "memory");
                    asm volatile("prefetch.tensormap [%0];" ::"l"(&wo_map) : "memory");
                }
                due += T_K;
                kp += 16384;
                bar += 8;
                dst = (i == 3) ? sb : dst + SLOT;
            }
#pragma unroll 1
            for (int k = 0; k < 16; k++) {
                mbar_expect_tx(bar, 8192);
                mbar_wait(empty + 8 * (4 + (k >> 1)));
                const int d = k - MIN_V;
                pace(due, vfull + 8 * (d < 0 ? (d >> 1) : d));
                tma3d(dst, &v_map, row, bar);
                due += k < 12 ? T_V : T_V2;
                row += 16;
                bar += 8;
                dst = (k == 3) ? sb : dst + 8192;
            }
            if (proj) {
                due += T_GAP;
                mbar_wait(empty + 8 * 12);
                mbar_wait(empty + 8 * 13);
#pragma unroll 1
                for (int n = 0; n < 4; n++) {
                    mbar_expect_tx(bar, 8192);
                    if (gk != 7) mbar_wait(bar - 8 * MAX_O);
                    pace(due, bar - 8);
                    tma4d(sb + n * 8192, &wo_map, c * 64, (n + c) & 3, (2 * gk + (r >= 7)) * 2, bar);
                    due += T_O;
                    bar += 8;
                }
            }
            mbar_wait(done);
            if (spins >= SPIN_LIMIT) __trap();
        }
        return;
    }

    const int w = warp - 1, j = threadIdx.x - 32;
    const int g = lane >> 2, t = lane & 3;

    if (w < 7) {
        cluster_arrive();
        cluster_wait();
        const uint32_t qa = sb + (w * 32 + (lane >> 4) * 8 + (lane & 7)) * 128;
        const uint32_t xa = sb + OFF_OB + (g & 3) * 896 + (cta & 1) * 448 + w * 64 + t * 4;
        mbar_wait(qfull);
        const uint32_t x0 = lds32(xa), x1 = lds32(xa + 16), x2 = lds32(xa + 32), x3 = lds32(xa + 48);
        float cq[4][4];
#pragma unroll
        for (int m = 0; m < 4; m++) {
            const uint32_t a = qa + (((2 * m + ((lane >> 3) & 1)) ^ (lane & 7)) << 4);
            const uint4 f0 = ldsm4t(a), f1 = ldsm4t(a + 2048);
            cq[m][0] = cq[m][1] = cq[m][2] = cq[m][3] = 0.f;
            mma16816(cq[m], f0, x0, x1);
            mma16816(cq[m], f1, x2, x3);
        }
        slot_release(empty + 8 * (w >> 2), fu(cq[0][0]) ^ fu(cq[1][0]) ^ fu(cq[2][0]) ^ fu(cq[3][0]), zero, lane);
        const int hf = t >> 1;
        const uint32_t qr = sb + OFF_QRED + w * 1024 + (t & 1) * 512 + hf * 128 + g * 16;
        sts128f(qr, hf ? cq[0][2] : cq[0][0], hf ? cq[1][2] : cq[1][0], hf ? cq[2][2] : cq[2][0], hf ? cq[3][2] : cq[3][0]);
        sts128f(qr + 256, hf ? cq[0][3] : cq[0][1], hf ? cq[1][3] : cq[1][1], hf ? cq[2][3] : cq[2][1], hf ? cq[3][3] : cq[3][1]);
    } else {
        if (lane == 0) {
#pragma unroll
            for (int i = 0; i < 28; i++) mbar_init(kfull + 8 * i, 1);
#pragma unroll
            for (int i = 0; i < 14; i++) mbar_init(empty + 8 * i, i == 1 ? 3 : (i < 10 ? 4 : 8));
#pragma unroll
            for (int i = 0; i < 7; i++) mbar_init(qbar + 8 * i, 1);
            mbar_init(done, 8);
            mbar_expect_tx(qbar, 4096);
            mbar_expect_tx(stbar, 64);
            mbar_expect_tx(obar, 2048);
#pragma unroll
            for (int i = 0; i < 4; i++) mbar_expect_tx(hbar + 8 * i, 512);
            fence_mbar_init();
        }
        __syncwarp();
        cluster_arrive();
        cluster_wait();
    }
    bar_compute();
    {
        const int pk = j >> 2;
        const uint32_t ra = sb + OFF_QRED + pk * 16;
        float4 a = lds128f(ra);
#pragma unroll
        for (int ww = 1; ww < 7; ww++) {
            const float4 v = lds128f(ra + ww * 1024);
            a.x += v.x; a.y += v.y; a.z += v.z; a.w += v.w;
        }
        const uint32_t dst = (pk >> 4) * 4 + (j & 3);
        st_async128(mapa(sb + OFF_QBUF + (r & 1) * 2048 + (r >> 1) * 256 + (pk & 15) * 16, dst),
                    fu(a.x), fu(a.y), fu(a.z), fu(a.w), mapa(qbar, dst));
        mbar_wait(qbar);
        const uint32_t qb = sb + OFF_QBUF + (j >> 5) * 256 + (j & 7) * 32 + ((j >> 3) & 3) * 4;
        const float q0 = lds32f(qb) + lds32f(qb + 2048), q1 = lds32f(qb + 16) + lds32f(qb + 2064);
        sts32(sb + OFF_QS + ((j >> 5) & 3) * 256 + (j & 1) * 128 + (j >> 7) * 64 + ((j >> 2) & 3) * 16 + ((j >> 4) & 1) * 8 + ((j >> 1) & 1) * 4,
              pack_bf16(q0, q1));
    }
    bar_compute();

    float s0 = 0.f, s1 = 0.f;
    {
        uint2 qf[8];
        const uint32_t qa = sb + OFF_QS + (g >> 2) * 128 + (g & 1) * 64 + t * 16;
        const uint32_t qx = ((g >> 1) & 1) * 8;
#pragma unroll
        for (int i = 0; i < 8; i++) qf[i] = lds64(qa + (i >> 1) * 256 + (((i & 1) * 8) ^ qx));
        const uint32_t kx = (g & 1) * 64;
        const uint32_t krow = sb + ((w & 3) * 8 + g) * 512 + t * 16;
        const int src = (lane & 28) + (g & 1);
#pragma unroll 1
        for (int k = 0; k < 4; k++) {
            const int ch = 2 * k + (w >> 2);
            const uint32_t ka = krow + (ch >= 4 ? ch - 4 : ch + 2) * SLOT;
            mbar_wait(kfull + 8 * ch);
            float a0[4] = {0.f, 0.f, 0.f, 0.f}, a1[4] = {0.f, 0.f, 0.f, 0.f};
#pragma unroll
            for (int i = 0; i < 8; i += 2) {
                const uint4 r0 = lds128(ka + ((i * 64) ^ kx)), r1 = lds128(ka + (((i + 1) * 64) ^ kx));
                mma16816(a0, r0, qf[i].x, qf[i].y);
                mma16816(a1, r1, qf[i + 1].x, qf[i + 1].y);
            }
            const float e0 = __shfl_sync(0xffffffffu, a0[0] + a1[0], src) + __shfl_sync(0xffffffffu, a0[2] + a1[2], src + 2);
            const float e1 = __shfl_sync(0xffffffffu, a0[1] + a1[1], src) + __shfl_sync(0xffffffffu, a0[3] + a1[3], src + 2);
            slot_release(empty + 8 * (2 + ch), fu(e0), zero, lane);
            if (t == k) { s0 = e0; s1 = e1; }
        }
    }
    float Mown;
    {
        s0 = round_bf16(s0);
        s1 = round_bf16(s1);
        float m0 = s0, m1 = s1;
#pragma unroll
        for (int o = 16; o > 0; o >>= 1) {
            m0 = fmaxf(m0, __shfl_xor_sync(0xffffffffu, m0, o));
            m1 = fmaxf(m1, __shfl_xor_sync(0xffffffffu, m1, o));
        }
        if (lane < 2) sts32(sb + OFF_WST + (w * 2 + lane) * 4, fu(lane ? m1 : m0));
        bar_compute();
        const float4 u0 = lds128f(sb + OFF_WST), u1 = lds128f(sb + OFF_WST + 16), u2 = lds128f(sb + OFF_WST + 32), u3 = lds128f(sb + OFF_WST + 48);
        const float M0 = fmaxf(fmaxf(fmaxf(u0.x, u0.z), fmaxf(u1.x, u1.z)), fmaxf(fmaxf(u2.x, u2.z), fmaxf(u3.x, u3.z)));
        const float M1 = fmaxf(fmaxf(fmaxf(u0.y, u0.w), fmaxf(u1.y, u1.w)), fmaxf(fmaxf(u2.y, u2.w), fmaxf(u3.y, u3.w)));
        Mown = (t & 1) ? M1 : M0;
        const uint32_t p = pack_bf16(exp_score(s0 - M0), exp_score(s1 - M1));
        const uint32_t pa = sb + OFF_PS + (4 * t + (w >> 1)) * 64 + (g >> 1) * 8 + (w & 1) * 4 + (g & 1) * 2;
        sts16(pa, (unsigned short)(p & 0xFFFFu));
        sts16(pa + 32, (unsigned short)(p >> 16));
        float l0 = __uint_as_float(p << 16), l1 = __uint_as_float(p & 0xFFFF0000u);
#pragma unroll
        for (int o = 16; o > 0; o >>= 1) {
            l0 += __shfl_xor_sync(0xffffffffu, l0, o);
            l1 += __shfl_xor_sync(0xffffffffu, l1, o);
        }
        if (lane < 2) sts32(sb + OFF_WST + 64 + (w * 2 + lane) * 4, fu(lane ? l1 : l0));
        bar_compute();
        if (j < 4) {
            const float4 v0 = lds128f(sb + OFF_WST + 64), v1 = lds128f(sb + OFF_WST + 80), v2 = lds128f(sb + OFF_WST + 96), v3 = lds128f(sb + OFF_WST + 112);
            const float L0 = ((v0.x + v0.z) + (v1.x + v1.z)) + ((v2.x + v2.z) + (v3.x + v3.z));
            const float L1 = ((v0.y + v0.w) + (v1.y + v1.w)) + ((v2.y + v2.w) + (v3.y + v3.w));
            st_async128(mapa(sb + OFF_WST + 128 + s * 16, b * 4 + j), fu(M0), fu(L0), fu(M1), fu(L1), mapa(stbar, b * 4 + j));
        }
    }

    const uint32_t h1_dst = pin(mapa(sb + OFF_HOP + r * 128 + (t >> 1) * 64 + g * 8, (t & 1) * 8 + w));
    const uint32_t h1_bar = pin(mapa(hbar + 8 * b, (t & 1) * 8 + w));
    const uint32_t h2_grp = (w >> 2) * 4 + (lane >> 3);
    const uint32_t h2_rank = h2_grp < 7 ? (r >> 3) * 7 + h2_grp : 14 + (r >> 3);
    const uint32_t h2_dst = pin(mapa(sb + OFF_OB + (w & 3) * OB_STRIDE + ((r - h2_grp) & 3) * 128 + ((r >> 2) & 1) * 64 +
                                     (lane & 3) * 16 + ((lane >> 2) & 1) * 8, h2_rank));
    const uint32_t h2_bar = pin(mapa(obar, h2_rank));
    const uint32_t h2_src = pin(sb + OFF_HOP + (w & 3) * 512 + (lane & 7) * 16);
    const uint32_t h2_wait = pin(hbar + 8 * (w & 3));
    const uint32_t bars = pin(obar);
    const uint32_t wo_src = pin(sb + (((lane >> 3) & 1) * 16 + (lane >> 4) * 8 + (lane & 7)) * 128 + ((w ^ (lane & 7)) << 4));
    const uint32_t ob_src = pin(sb + OFF_OB + (g & 3) * OB_STRIDE + (g >> 2) * 64 + t * 16);
    unsigned long long* acc_p = pin_ptr(acc + (c * 16 + (j >> 4)) * 32 + (j & 15));
    __nv_bfloat16* out_p = pin_ptr(out + (g & 3) * 448 + c * 64 + w * 8 + 2 * t + (g >> 2));
    const uint32_t k_one = pin(zero + 1u);
    const bool t_hi = pin(t >> 1) != 0, g_hi = pin(g >> 2) != 0, proj_on = pin(proj ? 1u : 0u) != 0;

    float acc0[4] = {0.f, 0.f, 0.f, 0.f}, acc1[4] = {0.f, 0.f, 0.f, 0.f};
    float wgt;
    {
        const uint32_t va0 = pin(sb + (w >> 1) * 2048 + ((lane >> 4) * 8 + (lane & 7)) * 128 + ((((w & 1) * 4 + ((lane >> 3) & 1)) ^ (lane & 7)) << 4));
        const uint32_t va1 = pin(va0 ^ 32);
        const uint32_t pa = pin(sb + OFF_PS + ((g >> 1) & 1) * 32 + t * 8);
        const uint32_t vb = bars - (obar - vfull);
#pragma unroll 1
        for (int k = 0; k < 8; k += 2) {
            const uint32_t so = (k < 4 ? k + 8 : k - 4) * 8192;
            const uint2 p0 = lds64(pa + k * 64), p1 = lds64(pa + k * 64 + 64);
            mbar_wait(vb + 8 * k);
            const uint4 f0 = ldsm4t(va0 + so), f1 = ldsm4t(va1 + so);
            mma16816(acc0, f0, p0.x, p0.y);
            mma16816(acc1, f1, p0.x, p0.y);
            mbar_wait(vb + 8 * k + 8);
            const uint4 f2 = ldsm4t(va0 + so + 8192), f3 = ldsm4t(va1 + so + 8192);
            mma16816(acc0, f2, p1.x, p1.y);
            mma16816(acc1, f3, p1.x, p1.y);
            slot_release(empty + 8 * (10 + (k >> 1)), fu(acc0[0]) ^ fu(acc1[0]), zero, lane);
        }
        uint2 pw[8];
#pragma unroll
        for (int k = 8; k < 16; k++) pw[k - 8] = lds64(pa + k * 64);
        {
            mbar_wait(stbar);
            const uint32_t sa = sb + OFF_WST + 128 + (t & 1) * 8;
            const float2 z0 = lds64f(sa), z1 = lds64f(sa + 16), z2 = lds64f(sa + 32), z3 = lds64f(sa + 48);
            const float mx = fmaxf(fmaxf(z0.x, z1.x), fmaxf(z2.x, z3.x));
            const float W = (exp_score(z0.x - mx) * z0.y + exp_score(z1.x - mx) * z1.y) +
                            (exp_score(z2.x - mx) * z2.y + exp_score(z3.x - mx) * z3.y);
            wgt = __uint_as_float(pin(fu(__fdividef(exp_score(Mown - mx), W))));
        }
        uint4 f0, f1;
#pragma unroll
        for (int k = 8; k < 16; k++) {
            mbar_wait_fast(vb + 8 * k);
            const uint4 n0 = ldsm4t(va0 + (k - 4) * 8192), n1 = ldsm4t(va1 + (k - 4) * 8192);
            if (k > 8) {
                mma16816(acc0, f0, pw[k - 9].x, pw[k - 9].y);
                mma16816(acc1, f1, pw[k - 9].x, pw[k - 9].y);
            }
            f0 = n0; f1 = n1;
        }
        mma16816(acc0, f0, pw[7].x, pw[7].y);
        mma16816(acc1, f1, pw[7].x, pw[7].y);
    }
    st_async64(h1_dst, fu((t_hi ? acc1[0] : acc0[0]) * wgt), fu((t_hi ? acc1[2] : acc0[2]) * wgt), h1_bar);
    {
        mbar_wait_fast(h2_wait);
        const float4 v0 = lds128f(h2_src), v1 = lds128f(h2_src + 128), v2 = lds128f(h2_src + 256), v3 = lds128f(h2_src + 384);
        st_async64(h2_dst, pack_bf16((v0.x + v1.x) + (v2.x + v3.x), (v0.z + v1.z) + (v2.z + v3.z)),
                   pack_bf16((v0.y + v1.y) + (v2.y + v3.y), (v0.w + v1.w) + (v2.w + v3.w)), h2_bar);
    }
    if (!proj_on) {
        mbar_wait_fast(bars);
        slot_release(bars + (done - obar), 0u, 0u, lane);
        return;
    }
    float sum;
    {
        const uint32_t ob = bars - (obar - ofull);
        float x0[4] = {0.f, 0.f, 0.f, 0.f}, x1[4] = {0.f, 0.f, 0.f, 0.f}, y0[4] = {0.f, 0.f, 0.f, 0.f}, y1[4] = {0.f, 0.f, 0.f, 0.f};
        uint4 bp[4], bq[4], oa[4];
#pragma unroll
        for (int n = 0; n < 3; n++) {
            mbar_wait_fast(ob + 8 * n);
            bp[n] = ldsm4t(wo_src + n * 8192);
            bq[n] = ldsm4t(wo_src + n * 8192 + 4096);
        }
        mbar_wait_fast(bars);
#pragma unroll
        for (int n = 0; n < 4; n++) oa[n] = lds128(ob_src + n * 128);
#pragma unroll
        for (int n = 0; n < 4; n++) {
            if (n == 3) {
                mbar_wait_fast(ob + 24);
                bp[3] = ldsm4t(wo_src + 3 * 8192);
                bq[3] = ldsm4t(wo_src + 3 * 8192 + 4096);
            }
            mma16816(x0, oa[n], bp[n].x, bp[n].y);
            mma16816(y0, oa[n], bp[n].z, bp[n].w);
            mma16816(x1, oa[n], bq[n].x, bq[n].y);
            mma16816(y1, oa[n], bq[n].z, bq[n].w);
        }
        float keep = x0[0] + y0[2], send = x0[1] + y0[3];
        if (g_hi) { send = x1[0] + y1[2]; keep = x1[1] + y1[3]; }
        sum = keep + __shfl_xor_sync(0xffffffffu, send, 16);
    }
    const uint32_t bits = fu(sum);
    const uint32_t sh = 129u - ((bits >> 23) & 0xFFu);
    const uint32_t smant = (((bits << 3) & 0x3FFFFF8u) | 0x4000000u) ^ (uint32_t)((int)bits >> 31);
    long long fx;
    asm("shr.s64 %0, %1, %2;" : "=l"(fx) : "l"((long long)((unsigned long long)smant << 32)), "r"(sh));
    const unsigned long long inc = ((unsigned long long)fx & 0xFFFFFFFF00000000ull) | (((uint32_t)fx & ~0x3FFu) | k_one);
    const bool fast = __any_sync(0xffffffffu, fabsf(sum) >= 0x1p-22f) && fabsf(sum) < 8.0f;
    unsigned long long tot = 0ull;
    asm volatile("{\n.reg .pred p;\nsetp.ne.u32 p, %3, 0;\n@p atom.relaxed.gpu.global.add.u64 %0, [%1], %2;\n}"
                 : "+l"(tot) : "l"(acc_p), "l"(inc), "r"((uint32_t)fast) : "memory");
    slot_release(bars + (done - obar), 0u, 0u, lane);
    if (!fast) { accumulate_slow(sum, acc_p, out_p); return; }
    tot += inc;
    const uint32_t cnt = (uint32_t)tot & 0x3FFu;
    asm volatile("{\n.reg .pred p;\nsetp.eq.u32 p, %3, 16;\n@p st.global.u16 [%0], %1;\n@p st.global.u64 [%2], 0;\n}"
                 ::"l"(out_p), "h"(__bfloat16_as_ushort(__float2bfloat16(acc_value(tot)))), "l"(acc_p), "r"(cnt) : "memory");
    if (cnt > 16u) finish_with_side(tot, acc_p, out_p);
}

typedef CUresult (*EncodeFn)(CUtensorMap*, CUtensorMapDataType, cuuint32_t, void*, const cuuint64_t*, const cuuint64_t*,
                             const cuuint32_t*, const cuuint32_t*, CUtensorMapInterleave, CUtensorMapSwizzle,
                             CUtensorMapL2promotion, CUtensorMapFloatOOBfill);

}

extern "C" void kernel_launch(void* const* d_in, const int* in_sizes, int n_in, void* d_out, int out_size) {
    (void)in_sizes; (void)n_in; (void)out_size;
    static EncodeFn encode = nullptr;
    static void* acc = nullptr;
    if (!encode) {
        cudaDriverEntryPointQueryResult qr;
        cudaGetDriverEntryPoint("cuTensorMapEncodeTiled", (void**)&encode, cudaEnableDefault, &qr);
        cudaGetSymbolAddress(&acc, g_acc);
        cudaFuncSetAttribute(decode_kernel, cudaFuncAttributeMaxDynamicSharedMemorySize, SMEM_BYTES);
        cudaFuncSetAttribute(decode_kernel, cudaFuncAttributeNonPortableClusterSizeAllowed, 1);
    }
    const cuuint32_t estr[4] = {1, 1, 1, 1};
    CUtensorMap wq_map, wo_map, v_map;
    {
        const cuuint64_t dim[2] = {4096, 448}, str[1] = {8192};
        const cuuint32_t box[2] = {64, 224};
        encode(&wq_map, CU_TENSOR_MAP_DATA_TYPE_BFLOAT16, 2, d_in[3], dim, str, box, estr, CU_TENSOR_MAP_INTERLEAVE_NONE,
               CU_TENSOR_MAP_SWIZZLE_128B, CU_TENSOR_MAP_L2_PROMOTION_NONE, CU_TENSOR_MAP_FLOAT_OOB_FILL_NONE);
    }
    {
        const cuuint64_t dim[4] = {448, 32, 4, 32}, str[3] = {896, 896 * 32, 896 * 128};
        const cuuint32_t box[4] = {64, 32, 1, 2};
        encode(&wo_map, CU_TENSOR_MAP_DATA_TYPE_BFLOAT16, 4, d_in[4], dim, str, box, estr, CU_TENSOR_MAP_INTERLEAVE_NONE,
               CU_TENSOR_MAP_SWIZZLE_128B, CU_TENSOR_MAP_L2_PROMOTION_NONE, CU_TENSOR_MAP_FLOAT_OOB_FILL_NONE);
    }
    {
        const cuuint64_t dim[3] = {64, 4ull * 8 * SK, 4}, str[2] = {512, 128};
        const cuuint32_t box[3] = {64, 16, 4};
        encode(&v_map, CU_TENSOR_MAP_DATA_TYPE_BFLOAT16, 3, d_in[2], dim, str, box, estr, CU_TENSOR_MAP_INTERLEAVE_NONE,
               CU_TENSOR_MAP_SWIZZLE_128B, CU_TENSOR_MAP_L2_PROMOTION_NONE, CU_TENSOR_MAP_FLOAT_OOB_FILL_NONE);
    }
    cudaLaunchConfig_t cfg = {};
    cfg.gridDim = dim3(128);
    cfg.blockDim = dim3(NTHREADS);
    cfg.dynamicSmemBytes = SMEM_BYTES;
    cfg.stream = cudaStreamPerThread;
    cudaLaunchAttribute attr[2];
    attr[0].id = cudaLaunchAttributeClusterDimension;
    attr[0].val.clusterDim.x = 16; attr[0].val.clusterDim.y = 1; attr[0].val.clusterDim.z = 1;
    attr[1].id = cudaLaunchAttributeClusterSchedulingPolicyPreference;
    attr[1].val.clusterSchedulingPolicyPreference = cudaClusterSchedulingPolicyLoadBalancing;
    cfg.attrs = attr;
    cfg.numAttrs = 2;
    cudaLaunchKernelEx(&cfg, decode_kernel, (const __nv_bfloat16*)d_in[0], (const __nv_bfloat16*)d_in[1],
                       (const __nv_bfloat16*)d_in[3], (__nv_bfloat16*)d_out, (unsigned long long*)acc, 0u,
                       wq_map, wo_map, v_map);
}
```

```cpp
#include <cuda_runtime.h>
#include <cuda_bf16.h>
#include <cuda.h>
#include <stdint.h>

namespace {

constexpr int SK = 4096, WIN0 = 3072;
constexpr int SLOT = 16384;
constexpr int OFF_BAR  = 6 * SLOT;
constexpr int OFF_QBUF = OFF_BAR + 416;
constexpr int OFF_QS   = OFF_QBUF + 4096;
constexpr int OFF_WST  = OFF_QS + 1024;
constexpr int OB_STRIDE = 576;
constexpr int OFF_OB   = OFF_WST + 192;
constexpr int OFF_HOP  = OFF_OB + 4 * OB_STRIDE;
constexpr int OFF_QRED = OFF_HOP + 2048;
constexpr int OFF_PS   = OFF_QRED;
constexpr int SMEM_BYTES = OFF_QRED + 7 * 1024;
static_assert(SMEM_BYTES <= 115712, "two CTAs must fit on one SM");
constexpr int NTHREADS = 288;
constexpr int SPIN_LIMIT = 1 << 20;

constexpr int T_K0   = 330;
constexpr int T_K    = 670;
constexpr int T_V    = 345;
constexpr int T_V2   = 300;
constexpr int T_GAP  = 30;
constexpr int T_O    = 300;
constexpr int T_LEAD = 1600;
constexpr int T_FAR  = 150;
constexpr int MIN_K = 2, MIN_V = 4;
constexpr int MAX_O = 6;

constexpr int ACC_WORDS = 8192;
__device__ __align__(32768) unsigned long long g_acc[ACC_WORDS];
__device__ float g_side[ACC_WORDS];

__device__ __forceinline__ void mbar_init(uint32_t bar, uint32_t cnt) {
    asm volatile("mbarrier.init.shared::cta.b64 [%0], %1;" ::"r"(bar), "r"(cnt) : "memory");
}
__device__ __forceinline__ void mbar_expect_tx(uint32_t bar, uint32_t bytes) {
    asm volatile("mbarrier.arrive.expect_tx.shared::cta.b64 _, [%0], %1;" ::"r"(bar), "r"(bytes) : "memory");
}
__device__ __forceinline__ void slot_release(uint32_t bar, uint32_t dep, uint32_t zero, int lane) {
    if (lane == 0) asm volatile("mbarrier.arrive.shared::cta.b64 _, [%0];" ::"r"(bar + (dep & zero)) : "memory");
}
__device__ __forceinline__ void mbar_wait_n(uint32_t bar, uint32_t& n) {
    asm volatile("{\n.reg .pred p, q;\n"
                 "WAIT_LOOP:\n"
                 "mbarrier.try_wait.parity.shared::cta.b64 p, [%1], 0;\n"
                 "add.u32 %0, %0, 1;\n"
                 "setp.lt.and.u32 q, %0, %2, !p;\n"
                 "@q bra.uni WAIT_LOOP;\n}"
                 : "+r"(n) : "r"(bar), "n"(SPIN_LIMIT) : "memory");
}
#define mbar_wait(bar) mbar_wait_n(bar, spins)
__device__ __forceinline__ void mbar_wait_fast(uint32_t bar) {
    asm volatile("{\n.reg .pred p;\nWAIT_LOOP:\nmbarrier.try_wait.parity.shared::cta.b64 p, [%0], 0;\n@!p bra.uni WAIT_LOOP;\n}"
                 ::"r"(bar) : "memory");
}
__device__ __forceinline__ uint32_t now_ns() {
    uint32_t t;
    asm volatile("mov.u32 %0, %%globaltimer_lo;" : "=r"(t)::"memory");
    return t;
}
__device__ __forceinline__ void pace(uint32_t due, uint32_t bar) {
    while ((int)(now_ns() - due) < 0) {
        uint32_t ok;
        asm volatile("{\n.reg .pred p;\nmbarrier.test_wait.parity.shared::cta.b64 p, [%1], 0;\nselp.u32 %0, 1, 0, p;\n}"
                     : "=r"(ok) : "r"(bar) : "memory");
        if (ok) break;
    }
}
__device__ __forceinline__ void bulk_g2s(uint32_t dst, const void* src, uint32_t bytes, uint32_t bar) {
    asm volatile("cp.async.bulk.shared::cluster.global.mbarrier::complete_tx::bytes [%0], [%1], %2, [%3];"
                 ::"r"(dst), "l"(src), "r"(bytes), "r"(bar) : "memory");
}
__device__ __forceinline__ void bulk_g2s_mc(uint32_t dst, const void* src, uint32_t bytes, uint32_t bar, uint16_t mask) {
    asm volatile("cp.async.bulk.shared::cluster.global.mbarrier::complete_tx::bytes.multicast::cluster [%0], [%1], %2, [%3], %4;"
                 ::"r"(dst), "l"(src), "r"(bytes), "r"(bar), "h"(mask) : "memory");
}
__device__ __forceinline__ void tma2d(uint32_t dst, const CUtensorMap* tm, int c0, int c1, uint32_t bar) {
    asm volatile("cp.async.bulk.tensor.2d.shared::cluster.global.mbarrier::complete_tx::bytes [%0], [%1, {%3, %4}], [%2];"
                 ::"r"(dst), "l"(tm), "r"(bar), "r"(c0), "r"(c1) : "memory");
}
__device__ __forceinline__ void tma3d(uint32_t dst, const CUtensorMap* tm, int c1, uint32_t bar) {
    asm volatile("cp.async.bulk.tensor.3d.shared::cluster.global.mbarrier::complete_tx::bytes [%0], [%1, {%3, %4, %3}], [%2];"
                 ::"r"(dst), "l"(tm), "r"(bar), "r"(0), "r"(c1) : "memory");
}
__device__ __forceinline__ void tma4d(uint32_t dst, const CUtensorMap* tm, int c0, int c2, int c3, uint32_t bar) {
    asm volatile("cp.async.bulk.tensor.4d.shared::cluster.global.mbarrier::complete_tx::bytes [%0], [%1, {%3, %4, %5, %6}], [%2];"
                 ::"r"(dst), "l"(tm), "r"(bar), "r"(c0), "r"(0), "r"(c2), "r"(c3) : "memory");
}
__device__ __forceinline__ uint32_t pin(uint32_t v) {
    uint32_t o;
    asm volatile("shfl.sync.bfly.b32 %0, %1, 0, 0x1f, 0xffffffff;" : "=r"(o) : "r"(v));
    return o;
}
template <typename T> __device__ __forceinline__ T* pin_ptr(T* p) {
    const unsigned long long a = (unsigned long long)p;
    return (T*)(((unsigned long long)pin((uint32_t)(a >> 32)) << 32) | pin((uint32_t)a));
}
__device__ __forceinline__ bool elect_one() {
    uint32_t p;
    asm volatile("{\n.reg .pred P;\nelect.sync _|P, 0xffffffff;\nselp.u32 %0, 1, 0, P;\n}" : "=r"(p));
    return p != 0;
}
__device__ __forceinline__ void bar_compute() { asm volatile("bar.sync 1, 256;" ::: "memory"); }
__device__ __forceinline__ void cluster_arrive() { asm volatile("barrier.cluster.arrive.relaxed.aligned;" ::: "memory"); }
__device__ __forceinline__ void cluster_wait() { asm volatile("barrier.cluster.wait.aligned;" ::: "memory"); }
__device__ __forceinline__ void fence_mbar_init() { asm volatile("fence.mbarrier_init.release.cluster;" ::: "memory"); }
__device__ __forceinline__ uint32_t mapa(uint32_t a, uint32_t rank) {
    uint32_t o;
    asm("mapa.shared::cluster.u32 %0, %1, %2;" : "=r"(o) : "r"(a), "r"(rank));
    return o;
}
__device__ __forceinline__ void st_async128(uint32_t a, uint32_t x, uint32_t y, uint32_t z, uint32_t w, uint32_t bar) {
    asm volatile("st.async.shared::cluster.mbarrier::complete_tx::bytes.v4.b32 [%0], {%1,%2,%3,%4}, [%5];"
                 ::"r"(a), "r"(x), "r"(y), "r"(z), "r"(w), "r"(bar) : "memory");
}
__device__ __forceinline__ void st_async64(uint32_t a, uint32_t x, uint32_t y, uint32_t bar) {
    asm volatile("st.async.shared::cluster.mbarrier::complete_tx::bytes.v2.b32 [%0], {%1,%2}, [%3];"
                 ::"r"(a), "r"(x), "r"(y), "r"(bar) : "memory");
}
__device__ __forceinline__ void mma16816(float (&c)[4], const uint4& a, uint32_t b0, uint32_t b1) {
    asm volatile("mma.sync.aligned.m16n8k16.row.col.f32.bf16.bf16.f32 {%0,%1,%2,%3}, {%4,%5,%6,%7}, {%8,%9}, {%0,%1,%2,%3};"
                 : "+f"(c[0]), "+f"(c[1]), "+f"(c[2]), "+f"(c[3])
                 : "r"(a.x), "r"(a.y), "r"(a.z), "r"(a.w), "r"(b0), "r"(b1));
}
__device__ __forceinline__ uint4 lds128(uint32_t a) {
    uint4 v;
    asm volatile("ld.shared.v4.u32 {%0,%1,%2,%3}, [%4];" : "=r"(v.x), "=r"(v.y), "=r"(v.z), "=r"(v.w) : "r"(a) : "memory");
    return v;
}
__device__ __forceinline__ float4 lds128f(uint32_t a) {
    float4 v;
    asm volatile("ld.shared.v4.f32 {%0,%1,%2,%3}, [%4];" : "=f"(v.x), "=f"(v.y), "=f"(v.z), "=f"(v.w) : "r"(a) : "memory");
    return v;
}
__device__ __forceinline__ float2 lds64f(uint32_t a) {
    float2 v;
    asm volatile("ld.shared.v2.f32 {%0,%1}, [%2];" : "=f"(v.x), "=f"(v.y) : "r"(a) : "memory");
    return v;
}
__device__ __forceinline__ uint2 lds64(uint32_t a) {
    uint2 v;
    asm volatile("ld.shared.v2.u32 {%0,%1}, [%2];" : "=r"(v.x), "=r"(v.y) : "r"(a) : "memory");
    return v;
}
__device__ __forceinline__ uint32_t lds32(uint32_t a) {
    uint32_t v;
    asm volatile("ld.shared.u32 %0, [%1];" : "=r"(v) : "r"(a) : "memory");
    return v;
}
__device__ __forceinline__ float lds32f(uint32_t a) { return __uint_as_float(lds32(a)); }
__device__ __forceinline__ void sts128f(uint32_t a, float x, float y, float z, float w) {
    asm volatile("st.shared.v4.f32 [%0], {%1,%2,%3,%4};" ::"r"(a), "f"(x), "f"(y), "f"(z), "f"(w) : "memory");
}
__device__ __forceinline__ void sts32(uint32_t a, uint32_t v) {
    asm volatile("st.shared.u32 [%0], %1;" ::"r"(a), "r"(v) : "memory");
}
__device__ __forceinline__ void sts16(uint32_t a, unsigned short v) {
    asm volatile("st.shared.u16 [%0], %1;" ::"r"(a), "h"(v) : "memory");
}
__device__ __forceinline__ uint4 ldsm4t(uint32_t a) {
    uint4 v;
    asm volatile("ldmatrix.sync.aligned.m8n8.x4.trans.shared.b16 {%0,%1,%2,%3}, [%4];"
                 : "=r"(v.x), "=r"(v.y), "=r"(v.z), "=r"(v.w) : "r"(a) : "memory");
    return v;
}
__device__ __forceinline__ uint32_t pack_bf16(float lo, float hi) {
    uint32_t r;
    asm("cvt.rn.bf16x2.f32 %0, %1, %2;" : "=r"(r) : "f"(hi), "f"(lo));
    return r;
}
__device__ __forceinline__ float round_bf16(float v) { return __uint_as_float(pack_bf16(0.f, v) & 0xFFFF0000u); }
__device__ __forceinline__ float exp_score(float d) {
    float y;
    asm("ex2.approx.ftz.f32 %0, %1;" : "=f"(y) : "f"(d * (0.0625f * 1.4426950408889634f)));
    return y;
}
__device__ __forceinline__ uint32_t fu(float v) { return __float_as_uint(v); }

__device__ __forceinline__ float acc_value(unsigned long long tot) {
    return fmaf((float)(int)(uint32_t)(tot >> 32), 0x1p-24f, (float)((uint32_t)tot >> 10) * 0x1p-46f);
}
__device__ __noinline__ void finish_with_side(unsigned long long tot, unsigned long long* acc_p, __nv_bfloat16* out_p) {
    if ((tot & 31ull) != 16ull) return;
    __threadfence();
    const float side = atomicExch(&g_side[acc_p - g_acc], 0.0f);
    *out_p = __float2bfloat16(acc_value(tot) + side);
    *acc_p = 0ull;
}
__device__ __noinline__ void accumulate_slow(float sum, unsigned long long* acc_p, __nv_bfloat16* out_p) {
    atomicAdd(&g_side[acc_p - g_acc], sum);
    __threadfence();
    finish_with_side(atomicAdd(acc_p, 33ull) + 33ull, acc_p, out_p);
}

__global__ void __launch_bounds__(NTHREADS, 2)
decode_kernel(const __nv_bfloat16* __restrict__ x, const __nv_bfloat16* __restrict__ kc,
              const __nv_bfloat16* __restrict__ wq, __nv_bfloat16* __restrict__ out,
              unsigned long long* __restrict__ acc, const uint32_t zero,
              const __grid_constant__ CUtensorMap wq_map, const __grid_constant__ CUtensorMap wo_map,
              const __grid_constant__ CUtensorMap v_map) {
    asm volatile("prefetch.global.L2 [%0];" ::"l"((const char*)wq + (blockIdx.x * 224 + min(threadIdx.x, 223u)) * 128));

    extern __shared__ __align__(1024) unsigned char smem[];
    const uint32_t sb = (uint32_t)__cvta_generic_to_shared(smem);
    const int warp = threadIdx.x >> 5, lane = threadIdx.x & 31;
    const int cta = blockIdx.x;
    const int gk = cta >> 4, r = cta & 15, b = r >> 2, s = r & 3;
    const bool proj = r < 14;
    const int c = r - 7 * (r >= 7);
    const uint32_t qfull = sb + OFF_BAR, kfull = qfull + 8, vfull = kfull + 64, ofull = vfull + 128, empty = ofull + 32;
    const uint32_t qbar = empty + 14 * 8, stbar = qbar + 8, obar = qbar + 16, hbar = qbar + 24, done = qbar + 56;
    uint32_t spins = 0;

    if (warp == 0) {
        const bool leader = elect_one();
        if (leader) {
            mbar_init(qfull, 1);
            mbar_expect_tx(qfull, 28672 + 3584);
            tma2d(sb, &wq_map, (cta >> 1) * 64, (cta & 1) * 224, qfull);
            fence_mbar_init();
        }
        uint32_t smid;
        asm volatile("mov.u32 %0, %%smid;" : "=r"(smid));
        const uint32_t gpc = smid < 64 ? (smid >> 1) & 7 : 1 + ((smid - 64) >> 1) % 7;
        uint32_t due = now_ns() + T_K0 - (gk == 7 ? T_LEAD : (gpc - 4u < 3u ? T_FAR : 0));
        __syncwarp();
        cluster_arrive();
        cluster_wait();
        if (leader) {
            if (proj) bulk_g2s_mc(sb + OFF_OB + r * 256, (const char*)x + r * 256, 256, qfull, (uint16_t)0xFFFF);
            int row = (b * 8 + gk) * SK + WIN0 + s * 256;
            const char* kp = (const char*)kc + (size_t)row * 512;
            uint32_t bar = kfull, dst = sb + 2 * SLOT;
#pragma unroll 1
            for (int i = 0; i < 8; i++) {
                mbar_expect_tx(bar, 16384);
                if (i >= 4) mbar_wait(empty + 8 * (i - 4));
                pace(due, i < MIN_K ? qfull : bar - 8 * MIN_K);
                bulk_g2s(dst, kp, 16384, bar);
                if (i == 1) {
                    asm volatile("prefetch.tensormap [%0];" ::"l"(&v_map) : "memory");
                    asm volatile("prefetch.tensormap [%0];" ::"l"(&wo_map) : "memory");
                }
                due += T_K;
                kp += 16384;
                bar += 8;
                dst = (i == 3) ? sb : dst + SLOT;
            }
#pragma unroll 1
            for (int k = 0; k < 16; k++) {
                mbar_expect_tx(bar, 8192);
                mbar_wait(empty + 8 * (4 + (k >> 1)));
                const int d = k - MIN_V;
                pace(due, vfull + 8 * (d < 0 ? (d >> 1) : d));
                tma3d(dst, &v_map, row, bar);
                due += k < 12 ? T_V : T_V2;
                row += 16;
                bar += 8;
                dst = (k == 3) ? sb : dst + 8192;
            }
            if (proj) {
                due += T_GAP;
                mbar_wait(empty + 8 * 12);
                mbar_wait(empty + 8 * 13);
#pragma unroll 1
                for (int n = 0; n < 4; n++) {
                    mbar_expect_tx(bar, 8192);
                    if (gk != 7) mbar_wait(bar - 8 * MAX_O);
                    pace(due, bar - 8);
                    tma4d(sb + n * 8192, &wo_map, c * 64, (n + c) & 3, (2 * gk + (r >= 7)) * 2, bar);
                    due += T_O;
                    bar += 8;
                }
            }
            mbar_wait(done);
            if (spins >= SPIN_LIMIT) __trap();
        }
        return;
    }

    const int w = warp - 1, j = threadIdx.x - 32;
    const int g = lane >> 2, t = lane & 3;

    if (w < 7) {
        cluster_arrive();
        cluster_wait();
        const uint32_t qa = sb + (w * 32 + (lane >> 4) * 8 + (lane & 7)) * 128;
        const uint32_t xa = sb + OFF_OB + (g & 3) * 896 + (cta & 1) * 448 + w * 64 + t * 4;
        mbar_wait(qfull);
        const uint32_t x0 = lds32(xa), x1 = lds32(xa + 16), x2 = lds32(xa + 32), x3 = lds32(xa + 48);
        float cq[4][4];
#pragma unroll
        for (int m = 0; m < 4; m++) {
            const uint32_t a = qa + (((2 * m + ((lane >> 3) & 1)) ^ (lane & 7)) << 4);
            const uint4 f0 = ldsm4t(a), f1 = ldsm4t(a + 2048);
            cq[m][0] = cq[m][1] = cq[m][2] = cq[m][3] = 0.f;
            mma16816(cq[m], f0, x0, x1);
            mma16816(cq[m], f1, x2, x3);
        }
        slot_release(empty + 8 * (w >> 2), fu(cq[0][0]) ^ fu(cq[1][0]) ^ fu(cq[2][0]) ^ fu(cq[3][0]), zero, lane);
        const int hf = t >> 1;
        const uint32_t qr = sb + OFF_QRED + w * 1024 + (t & 1) * 512 + hf * 128 + g * 16;
        sts128f(qr, hf ? cq[0][2] : cq[0][0], hf ? cq[1][2] : cq[1][0], hf ? cq[2][2] : cq[2][0], hf ? cq[3][2] : cq[3][0]);
        sts128f(qr + 256, hf ? cq[0][3] : cq[0][1], hf ? cq[1][3] : cq[1][1], hf ? cq[2][3] : cq[2][1], hf ? cq[3][3] : cq[3][1]);
    } else {
        if (lane == 0) {
#pragma unroll
            for (int i = 0; i < 28; i++) mbar_init(kfull + 8 * i, 1);
#pragma unroll
            for (int i = 0; i < 14; i++) mbar_init(empty + 8 * i, i == 1 ? 3 : (i < 10 ? 4 : 8));
#pragma unroll
            for (int i = 0; i < 7; i++) mbar_init(qbar + 8 * i, 1);
            mbar_init(done, 8);
            mbar_expect_tx(qbar, 4096);
            mbar_expect_tx(stbar, 64);
            mbar_expect_tx(obar, 2048);
#pragma unroll
            for (int i = 0; i < 4; i++) mbar_expect_tx(hbar + 8 * i, 512);
            fence_mbar_init();
        }
        __syncwarp();
        cluster_arrive();
        cluster_wait();
    }
    bar_compute();
    {
        const int pk = j >> 2;
        const uint32_t ra = sb + OFF_QRED + pk * 16;
        float4 a = lds128f(ra);
#pragma unroll
        for (int ww = 1; ww < 7; ww++) {
            const float4 v = lds128f(ra + ww * 1024);
            a.x += v.x; a.y += v.y; a.z += v.z; a.w += v.w;
        }
        const uint32_t dst = (pk >> 4) * 4 + (j & 3);
        st_async128(mapa(sb + OFF_QBUF + (r & 1) * 2048 + (r >> 1) * 256 + (pk & 15) * 16, dst),
                    fu(a.x), fu(a.y), fu(a.z), fu(a.w), mapa(qbar, dst));
        mbar_wait(qbar);
        const uint32_t qb = sb + OFF_QBUF + (j >> 5) * 256 + (j & 7) * 32 + ((j >> 3) & 3) * 4;
        const float q0 = lds32f(qb) + lds32f(qb + 2048), q1 = lds32f(qb + 16) + lds32f(qb + 2064);
        sts32(sb + OFF_QS + ((j >> 5) & 3) * 256 + (j & 1) * 128 + (j >> 7) * 64 + ((j >> 2) & 3) * 16 + ((j >> 4) & 1) * 8 + ((j >> 1) & 1) * 4,
              pack_bf16(q0, q1));
    }
    bar_compute();

    float s0 = 0.f, s1 = 0.f;
    {
        uint2 qf[8];
        const uint32_t qa = sb + OFF_QS + (g >> 2) * 128 + (g & 1) * 64 + t * 16;
        const uint32_t qx = ((g >> 1) & 1) * 8;
#pragma unroll
        for (int i = 0; i < 8; i++) qf[i] = lds64(qa + (i >> 1) * 256 + (((i & 1) * 8) ^ qx));
        const uint32_t kx = (g & 1) * 64;
        const uint32_t krow = sb + ((w & 3) * 8 + g) * 512 + t * 16;
        const int src = (lane & 28) + (g & 1);
#pragma unroll 1
        for (int k = 0; k < 4; k++) {
            const int ch = 2 * k + (w >> 2);
            const uint32_t ka = krow + (ch >= 4 ? ch - 4 : ch + 2) * SLOT;
            mbar_wait(kfull + 8 * ch);
            float a0[4] = {0.f, 0.f, 0.f, 0.f}, a1[4] = {0.f, 0.f, 0.f, 0.f};
#pragma unroll
            for (int i = 0; i < 8; i += 2) {
                const uint4 r0 = lds128(ka + ((i * 64) ^ kx)), r1 = lds128(ka + (((i + 1) * 64) ^ kx));
                mma16816(a0, r0, qf[i].x, qf[i].y);
                mma16816(a1, r1, qf[i + 1].x, qf[i + 1].y);
            }
            const float e0 = __shfl_sync(0xffffffffu, a0[0] + a1[0], src) + __shfl_sync(0xffffffffu, a0[2] + a1[2], src + 2);
            const float e1 = __shfl_sync(0xffffffffu, a0[1] + a1[1], src) + __shfl_sync(0xffffffffu, a0[3] + a1[3], src + 2);
            slot_release(empty + 8 * (2 + ch), fu(e0), zero, lane);
            if (t == k) { s0 = e0; s1 = e1; }
        }
    }
    float Mown;
    {
        s0 = round_bf16(s0);
        s1 = round_bf16(s1);
        float m0 = s0, m1 = s1;
#pragma unroll
        for (int o = 16; o > 0; o >>= 1) {
            m0 = fmaxf(m0, __shfl_xor_sync(0xffffffffu, m0, o));
            m1 = fmaxf(m1, __shfl_xor_sync(0xffffffffu, m1, o));
        }
        if (lane < 2) sts32(sb + OFF_WST + (w * 2 + lane) * 4, fu(lane ? m1 : m0));
        bar_compute();
        const float4 u0 = lds128f(sb + OFF_WST), u1 = lds128f(sb + OFF_WST + 16), u2 = lds128f(sb + OFF_WST + 32), u3 = lds128f(sb + OFF_WST + 48);
        const float M0 = fmaxf(fmaxf(fmaxf(u0.x, u0.z), fmaxf(u1.x, u1.z)), fmaxf(fmaxf(u2.x, u2.z), fmaxf(u3.x, u3.z)));
        const float M1 = fmaxf(fmaxf(fmaxf(u0.y, u0.w), fmaxf(u1.y, u1.w)), fmaxf(fmaxf(u2.y, u2.w), fmaxf(u3.y, u3.w)));
        Mown = (t & 1) ? M1 : M0;
        const uint32_t p = pack_bf16(exp_score(s0 - M0), exp_score(s1 - M1));
        const uint32_t pa = sb + OFF_PS + (4 * t + (w >> 1)) * 64 + (g >> 1) * 8 + (w & 1) * 4 + (g & 1) * 2;
        sts16(pa, (unsigned short)(p & 0xFFFFu));
        sts16(pa + 32, (unsigned short)(p >> 16));
        float l0 = __uint_as_float(p << 16), l1 = __uint_as_float(p & 0xFFFF0000u);
#pragma unroll
        for (int o = 16; o > 0; o >>= 1) {
            l0 += __shfl_xor_sync(0xffffffffu, l0, o);
            l1 += __shfl_xor_sync(0xffffffffu, l1, o);
        }
        if (lane < 2) sts32(sb + OFF_WST + 64 + (w * 2 + lane) * 4, fu(lane ? l1 : l0));
        bar_compute();
        if (j < 4) {
            const float4 v0 = lds128f(sb + OFF_WST + 64), v1 = lds128f(sb + OFF_WST + 80), v2 = lds128f(sb + OFF_WST + 96), v3 = lds128f(sb + OFF_WST + 112);
            const float L0 = ((v0.x + v0.z) + (v1.x + v1.z)) + ((v2.x + v2.z) + (v3.x + v3.z));
            const float L1 = ((v0.y + v0.w) + (v1.y + v1.w)) + ((v2.y + v2.w) + (v3.y + v3.w));
            st_async128(mapa(sb + OFF_WST + 128 + s * 16, b * 4 + j), fu(M0), fu(L0), fu(M1), fu(L1), mapa(stbar, b * 4 + j));
        }
    }

    const uint32_t h1_dst = pin(mapa(sb + OFF_HOP + r * 128 + (t >> 1) * 64 + g * 8, (t & 1) * 8 + w));
    const uint32_t h1_bar = pin(mapa(hbar + 8 * b, (t & 1) * 8 + w));
    const uint32_t h2_grp = (w >> 2) * 4 + (lane >> 3);
    const uint32_t h2_rank = h2_grp < 7 ? (r >> 3) * 7 + h2_grp : 14 + (r >> 3);
    const uint32_t h2_dst = pin(mapa(sb + OFF_OB + (w & 3) * OB_STRIDE + ((r - h2_grp) & 3) * 128 + ((r >> 2) & 1) * 64 +
                                     (lane & 3) * 16 + ((lane >> 2) & 1) * 8, h2_rank));
    const uint32_t h2_bar = pin(mapa(obar, h2_rank));
    const uint32_t h2_src = pin(sb + OFF_HOP + (w & 3) * 512 + (lane & 7) * 16);
    const uint32_t h2_wait = pin(hbar + 8 * (w & 3));
    const uint32_t bars = pin(obar);
    const uint32_t wo_src = pin(sb + (((lane >> 3) & 1) * 16 + (lane >> 4) * 8 + (lane & 7)) * 128 + ((w ^ (lane & 7)) << 4));
    const uint32_t ob_src = pin(sb + OFF_OB + (g & 3) * OB_STRIDE + (g >> 2) * 64 + t * 16);
    unsigned long long* acc_p = pin_ptr(acc + (c & 3) * 2048 + 512 + (c >> 2) * 512 + (j >> 4) * 32 + (j & 15));
    __nv_bfloat16* out_p = pin_ptr(out + (g & 3) * 448 + c * 64 + w * 8 + 2 * t + (g >> 2));
    const uint32_t k_one = pin(zero + 1u);
    const bool t_hi = pin(t >> 1) != 0, g_hi = pin(g >> 2) != 0, proj_on = pin(proj ? 1u : 0u) != 0;

    float acc0[4] = {0.f, 0.f, 0.f, 0.f}, acc1[4] = {0.f, 0.f, 0.f, 0.f};
    float wgt;
    {
        const uint32_t va0 = pin(sb + (w >> 1) * 2048 + ((lane >> 4) * 8 + (lane & 7)) * 128 + ((((w & 1) * 4 + ((lane >> 3) & 1)) ^ (lane & 7)) << 4));
        const uint32_t va1 = pin(va0 ^ 32);
        const uint32_t pa = pin(sb + OFF_PS + ((g >> 1) & 1) * 32 + t * 8);
        const uint32_t vb = bars - (obar - vfull);
#pragma unroll 1
        for (int k = 0; k < 8; k += 2) {
            const uint32_t so = (k < 4 ? k + 8 : k - 4) * 8192;
            const uint2 p0 = lds64(pa + k * 64), p1 = lds64(pa + k * 64 + 64);
            mbar_wait(vb + 8 * k);
            const uint4 f0 = ldsm4t(va0 + so), f1 = ldsm4t(va1 + so);
            mma16816(acc0, f0, p0.x, p0.y);
            mma16816(acc1, f1, p0.x, p0.y);
            mbar_wait(vb + 8 * k + 8);
            const uint4 f2 = ldsm4t(va0 + so + 8192), f3 = ldsm4t(va1 + so + 8192);
            mma16816(acc0, f2, p1.x, p1.y);
            mma16816(acc1, f3, p1.x, p1.y);
            slot_release(empty + 8 * (10 + (k >> 1)), fu(acc0[0]) ^ fu(acc1[0]), zero, lane);
        }
        uint2 pw[8];
#pragma unroll
        for (int k = 8; k < 16; k++) pw[k - 8] = lds64(pa + k * 64);
        {
            mbar_wait(stbar);
            const uint32_t sa = sb + OFF_WST + 128 + (t & 1) * 8;
            const float2 z0 = lds64f(sa), z1 = lds64f(sa + 16), z2 = lds64f(sa + 32), z3 = lds64f(sa + 48);
            const float mx = fmaxf(fmaxf(z0.x, z1.x), fmaxf(z2.x, z3.x));
            const float W = (exp_score(z0.x - mx) * z0.y + exp_score(z1.x - mx) * z1.y) +
                            (exp_score(z2.x - mx) * z2.y + exp_score(z3.x - mx) * z3.y);
            wgt = __uint_as_float(pin(fu(__fdividef(exp_score(Mown - mx), W))));
        }
        uint4 f0, f1;
#pragma unroll
        for (int k = 8; k < 16; k++) {
            mbar_wait_fast(vb + 8 * k);
            const uint4 n0 = ldsm4t(va0 + (k - 4) * 8192), n1 = ldsm4t(va1 + (k - 4) * 8192);
            if (k > 8) {
                mma16816(acc0, f0, pw[k - 9].x, pw[k - 9].y);
                mma16816(acc1, f1, pw[k - 9].x, pw[k - 9].y);
            }
            f0 = n0; f1 = n1;
        }
        mma16816(acc0, f0, pw[7].x, pw[7].y);
        mma16816(acc1, f1, pw[7].x, pw[7].y);
    }
    st_async64(h1_dst, fu((t_hi ? acc1[0] : acc0[0]) * wgt), fu((t_hi ? acc1[2] : acc0[2]) * wgt), h1_bar);
    {
        mbar_wait_fast(h2_wait);
        const float4 v0 = lds128f(h2_src), v1 = lds128f(h2_src + 128), v2 = lds128f(h2_src + 256), v3 = lds128f(h2_src + 384);
        st_async64(h2_dst, pack_bf16((v0.x + v1.x) + (v2.x + v3.x), (v0.z + v1.z) + (v2.z + v3.z)),
                   pack_bf16((v0.y + v1.y) + (v2.y + v3.y), (v0.w + v1.w) + (v2.w + v3.w)), h2_bar);
    }
    if (!proj_on) {
        mbar_wait_fast(bars);
        slot_release(bars + (done - obar), 0u, 0u, lane);
        return;
    }
    float sum;
    {
        const uint32_t ob = bars - (obar - ofull);
        float x0[4] = {0.f, 0.f, 0.f, 0.f}, x1[4] = {0.f, 0.f, 0.f, 0.f}, y0[4] = {0.f, 0.f, 0.f, 0.f}, y1[4] = {0.f, 0.f, 0.f, 0.f};
        uint4 bp[4], bq[4], oa[4];
#pragma unroll
        for (int n = 0; n < 3; n++) {
            mbar_wait_fast(ob + 8 * n);
            bp[n] = ldsm4t(wo_src + n * 8192);
            bq[n] = ldsm4t(wo_src + n * 8192 + 4096);
        }
        mbar_wait_fast(bars);
#pragma unroll
        for (int n = 0; n < 4; n++) oa[n] = lds128(ob_src + n * 128);
#pragma unroll
        for (int n = 0; n < 4; n++) {
            if (n == 3) {
                mbar_wait_fast(ob + 24);
                bp[3] = ldsm4t(wo_src + 3 * 8192);
                bq[3] = ldsm4t(wo_src + 3 * 8192 + 4096);
            }
            mma16816(x0, oa[n], bp[n].x, bp[n].y);
            mma16816(y0, oa[n], bp[n].z, bp[n].w);
            mma16816(x1, oa[n], bq[n].x, bq[n].y);
            mma16816(y1, oa[n], bq[n].z, bq[n].w);
        }
        float keep = x0[0] + y0[2], send = x0[1] + y0[3];
        if (g_hi) { send = x1[0] + y1[2]; keep = x1[1] + y1[3]; }
        sum = keep + __shfl_xor_sync(0xffffffffu, send, 16);
    }
    const uint32_t bits = fu(sum);
    const uint32_t sh = 129u - ((bits >> 23) & 0xFFu);
    const uint32_t smant = (((bits << 3) & 0x3FFFFF8u) | 0x4000000u) ^ (uint32_t)((int)bits >> 31);
    long long fx;
    asm("shr.s64 %0, %1, %2;" : "=l"(fx) : "l"((long long)((unsigned long long)smant << 32)), "r"(sh));
    const unsigned long long inc = ((unsigned long long)fx & 0xFFFFFFFF00000000ull) | (((uint32_t)fx & ~0x3FFu) | k_one);
    const bool fast = __any_sync(0xffffffffu, fabsf(sum) >= 0x1p-22f) && fabsf(sum) < 8.0f;
    unsigned long long tot = 0ull;
    asm volatile("{\n.reg .pred p;\nsetp.ne.u32 p, %3, 0;\n@p atom.relaxed.gpu.global.add.u64 %0, [%1], %2;\n}"
                 : "+l"(tot) : "l"(acc_p), "l"(inc), "r"((uint32_t)fast) : "memory");
    slot_release(bars + (done - obar), 0u, 0u, lane);
    if (!fast) { accumulate_slow(sum, acc_p, out_p); return; }
    tot += inc;
    const uint32_t cnt = (uint32_t)tot & 0x3FFu;
    asm volatile("{\n.reg .pred p;\nsetp.eq.u32 p, %3, 16;\n@p st.global.u16 [%0], %1;\n@p st.global.u64 [%2], 0;\n}"
                 ::"l"(out_p), "h"(__bfloat16_as_ushort(__float2bfloat16(acc_value(tot)))), "l"(acc_p), "r"(cnt) : "memory");
    if (cnt > 16u) finish_with_side(tot, acc_p, out_p);
}

typedef CUresult (*EncodeFn)(CUtensorMap*, CUtensorMapDataType, cuuint32_t, void*, const cuuint64_t*, const cuuint64_t*,
                             const cuuint32_t*, const cuuint32_t*, CUtensorMapInterleave, CUtensorMapSwizzle,
                             CUtensorMapL2promotion, CUtensorMapFloatOOBfill);

}

extern "C" void kernel_launch(void* const* d_in, const int* in_sizes, int n_in, void* d_out, int out_size) {
    (void)in_sizes; (void)n_in; (void)out_size;
    static EncodeFn encode = nullptr;
    static void* acc = nullptr;
    if (!encode) {
        cudaDriverEntryPointQueryResult qr;
        cudaGetDriverEntryPoint("cuTensorMapEncodeTiled", (void**)&encode, cudaEnableDefault, &qr);
        cudaGetSymbolAddress(&acc, g_acc);
        cudaFuncSetAttribute(decode_kernel, cudaFuncAttributeMaxDynamicSharedMemorySize, SMEM_BYTES);
        cudaFuncSetAttribute(decode_kernel, cudaFuncAttributeNonPortableClusterSizeAllowed, 1);
    }
    const cuuint32_t estr[4] = {1, 1, 1, 1};
    CUtensorMap wq_map, wo_map, v_map;
    {
        const cuuint64_t dim[2] = {4096, 448}, str[1] = {8192};
        const cuuint32_t box[2] = {64, 224};
        encode(&wq_map, CU_TENSOR_MAP_DATA_TYPE_BFLOAT16, 2, d_in[3], dim, str, box, estr, CU_TENSOR_MAP_INTERLEAVE_NONE,
               CU_TENSOR_MAP_SWIZZLE_128B, CU_TENSOR_MAP_L2_PROMOTION_NONE, CU_TENSOR_MAP_FLOAT_OOB_FILL_NONE);
    }
    {
        const cuuint64_t dim[4] = {448, 32, 4, 32}, str[3] = {896, 896 * 32, 896 * 128};
        const cuuint32_t box[4] = {64, 32, 1, 2};
        encode(&wo_map, CU_TENSOR_MAP_DATA_TYPE_BFLOAT16, 4, d_in[4], dim, str, box, estr, CU_TENSOR_MAP_INTERLEAVE_NONE,
               CU_TENSOR_MAP_SWIZZLE_128B, CU_TENSOR_MAP_L2_PROMOTION_NONE, CU_TENSOR_MAP_FLOAT_OOB_FILL_NONE);
    }
    {
        const cuuint64_t dim[3] = {64, 4ull * 8 * SK, 4}, str[2] = {512, 128};
        const cuuint32_t box[3] = {64, 16, 4};
        encode(&v_map, CU_TENSOR_MAP_DATA_TYPE_BFLOAT16, 3, d_in[2], dim, str, box, estr, CU_TENSOR_MAP_INTERLEAVE_NONE,
               CU_TENSOR_MAP_SWIZZLE_128B, CU_TENSOR_MAP_L2_PROMOTION_NONE, CU_TENSOR_MAP_FLOAT_OOB_FILL_NONE);
    }
    cudaLaunchConfig_t cfg = {};
    cfg.gridDim = dim3(128);
    cfg.blockDim = dim3(NTHREADS);
    cfg.dynamicSmemBytes = SMEM_BYTES;
    cfg.stream = cudaStreamPerThread;
    cudaLaunchAttribute attr[2];
    attr[0].id = cudaLaunchAttributeClusterDimension;
    attr[0].val.clusterDim.x = 16; attr[0].val.clusterDim.y = 1; attr[0].val.clusterDim.z = 1;
    attr[1].id = cudaLaunchAttributeClusterSchedulingPolicyPreference;
    attr[1].val.clusterSchedulingPolicyPreference = cudaClusterSchedulingPolicyLoadBalancing;
    cfg.attrs = attr;
    cfg.numAttrs = 2;
    cudaLaunchKernelEx(&cfg, decode_kernel, (const __nv_bfloat16*)d_in[0], (const __nv_bfloat16*)d_in[1],
                       (const __nv_bfloat16*)d_in[3], (__nv_bfloat16*)d_out, (unsigned long long*)acc, 0u,
                       wq_map, wo_map, v_map);
}
```

```cpp
#include <cuda_runtime.h>
#include <cuda_bf16.h>
#include <cuda.h>
#include <stdint.h>

namespace {

constexpr int SK = 4096, WIN0 = 3072;
constexpr int SLOT = 16384;
constexpr int OFF_QBUF = 6 * SLOT;
constexpr int OFF_QS   = OFF_QBUF + 4096;
constexpr int OB_STRIDE = 576;
constexpr int OFF_OB   = OFF_QS + 1024;
constexpr int OFF_HOP  = OFF_OB + 4 * OB_STRIDE;
constexpr int OFF_QRED = OFF_HOP + 2048;
constexpr int OFF_PS   = OFF_QRED;
constexpr int OFF_WST  = OFF_QRED + 7 * 1024;
constexpr int OFF_BAR  = OFF_WST + 192;
constexpr int SMEM_BYTES = OFF_BAR + 416;
static_assert(SMEM_BYTES <= 115712, "two CTAs must fit on one SM");
constexpr int NTHREADS = 288;
constexpr int SPIN_LIMIT = 1 << 20;

constexpr int T_K0   = 330;
constexpr int T_K    = 670;
constexpr int T_V    = 345;
constexpr int T_V2   = 300;
constexpr int T_GAP  = 30;
constexpr int T_O    = 300;
constexpr int T_LEAD = 1600;
constexpr int T_FAR  = 150;
constexpr int MIN_K = 2, MIN_V = 4;
constexpr int MAX_O = 6;

constexpr int ACC_WORDS = 8192;
__device__ __align__(32768) unsigned long long g_acc[ACC_WORDS];
__device__ float g_side[ACC_WORDS];

__device__ __forceinline__ void mbar_init(uint32_t bar, uint32_t cnt) {
    asm volatile("mbarrier.init.shared::cta.b64 [%0], %1;" ::"r"(bar), "r"(cnt) : "memory");
}
__device__ __forceinline__ void mbar_expect_tx(uint32_t bar, uint32_t bytes) {
    asm volatile("mbarrier.arrive.expect_tx.shared::cta.b64 _, [%0], %1;" ::"r"(bar), "r"(bytes) : "memory");
}
__device__ __forceinline__ void slot_release(uint32_t bar, uint32_t dep, uint32_t zero, int lane) {
    if (lane == 0) asm volatile("mbarrier.arrive.shared::cta.b64 _, [%0];" ::"r"(bar + (dep & zero)) : "memory");
}
__device__ __forceinline__ void mbar_wait_n(uint32_t bar, uint32_t& n) {
    asm volatile("{\n.reg .pred p, q;\n"
                 "WAIT_LOOP:\n"
                 "mbarrier.try_wait.parity.shared::cta.b64 p, [%1], 0;\n"
                 "add.u32 %0, %0, 1;\n"
                 "setp.lt.and.u32 q, %0, %2, !p;\n"
                 "@q bra.uni WAIT_LOOP;\n}"
                 : "+r"(n) : "r"(bar), "n"(SPIN_LIMIT) : "memory");
}
#define mbar_wait(bar) mbar_wait_n(bar, spins)
__device__ __forceinline__ void mbar_wait_fast(uint32_t bar) {
    asm volatile("{\n.reg .pred p;\nWAIT_LOOP:\nmbarrier.try_wait.parity.shared::cta.b64 p, [%0], 0;\n@!p bra.uni WAIT_LOOP;\n}"
                 ::"r"(bar) : "memory");
}
__device__ __forceinline__ uint32_t now_ns() {
    uint32_t t;
    asm volatile("mov.u32 %0, %%globaltimer_lo;" : "=r"(t)::"memory");
    return t;
}
__device__ __forceinline__ void pace(uint32_t due, uint32_t bar) {
    while ((int)(now_ns() - due) < 0) {
        uint32_t ok;
        asm volatile("{\n.reg .pred p;\nmbarrier.test_wait.parity.shared::cta.b64 p, [%1], 0;\nselp.u32 %0, 1, 0, p;\n}"
                     : "=r"(ok) : "r"(bar) : "memory");
        if (ok) break;
    }
}
__device__ __forceinline__ void bulk_g2s(uint32_t dst, const void* src, uint32_t bytes, uint32_t bar) {
    asm volatile("cp.async.bulk.shared::cluster.global.mbarrier::complete_tx::bytes [%0], [%1], %2, [%3];"
                 ::"r"(dst), "l"(src), "r"(bytes), "r"(bar) : "memory");
}
__device__ __forceinline__ void bulk_g2s_mc(uint32_t dst, const void* src, uint32_t bytes, uint32_t bar, uint16_t mask) {
    asm volatile("cp.async.bulk.shared::cluster.global.mbarrier::complete_tx::bytes.multicast::cluster [%0], [%1], %2, [%3], %4;"
                 ::"r"(dst), "l"(src), "r"(bytes), "r"(bar), "h"(mask) : "memory");
}
__device__ __forceinline__ void tma2d(uint32_t dst, const CUtensorMap* tm, int c0, int c1, uint32_t bar) {
    asm volatile("cp.async.bulk.tensor.2d.shared::cluster.global.mbarrier::complete_tx::bytes [%0], [%1, {%3, %4}], [%2];"
                 ::"r"(dst), "l"(tm), "r"(bar), "r"(c0), "r"(c1) : "memory");
}
__device__ __forceinline__ void tma3d(uint32_t dst, const CUtensorMap* tm, int c1, uint32_t bar) {
    asm volatile("cp.async.bulk.tensor.3d.shared::cluster.global.mbarrier::complete_tx::bytes [%0], [%1, {%3, %4, %3}], [%2];"
                 ::"r"(dst), "l"(tm), "r"(bar), "r"(0), "r"(c1) : "memory");
}
__device__ __forceinline__ void tma4d(uint32_t dst, const CUtensorMap* tm, int c0, int c2, int c3, uint32_t bar) {
    asm volatile("cp.async.bulk.tensor.4d.shared::cluster.global.mbarrier::complete_tx::bytes [%0], [%1, {%3, %4, %5, %6}], [%2];"
                 ::"r"(dst), "l"(tm), "r"(bar), "r"(c0), "r"(0), "r"(c2), "r"(c3) : "memory");
}
__device__ __forceinline__ uint32_t pin(uint32_t v) {
    uint32_t o;
    asm volatile("shfl.sync.bfly.b32 %0, %1, 0, 0x1f, 0xffffffff;" : "=r"(o) : "r"(v));
    return o;
}
template <typename T> __device__ __forceinline__ T* pin_ptr(T* p) {
    const unsigned long long a = (unsigned long long)p;
    return (T*)(((unsigned long long)pin((uint32_t)(a >> 32)) << 32) | pin((uint32_t)a));
}
__device__ __forceinline__ bool elect_one() {
    uint32_t p;
    asm volatile("{\n.reg .pred P;\nelect.sync _|P, 0xffffffff;\nselp.u32 %0, 1, 0, P;\n}" : "=r"(p));
    return p != 0;
}
__device__ __forceinline__ void bar_compute() { asm volatile("bar.sync 1, 256;" ::: "memory"); }
__device__ __forceinline__ void cluster_arrive() { asm volatile("barrier.cluster.arrive.relaxed.aligned;" ::: "memory"); }
__device__ __forceinline__ void cluster_wait() { asm volatile("barrier.cluster.wait.aligned;" ::: "memory"); }
__device__ __forceinline__ void fence_mbar_init() { asm volatile("fence.mbarrier_init.release.cluster;" ::: "memory"); }
__device__ __forceinline__ uint32_t mapa(uint32_t a, uint32_t rank) {
    uint32_t o;
    asm("mapa.shared::cluster.u32 %0, %1, %2;" : "=r"(o) : "r"(a), "r"(rank));
    return o;
}
__device__ __forceinline__ void st_async128(uint32_t a, uint32_t x, uint32_t y, uint32_t z, uint32_t w, uint32_t bar) {
    asm volatile("st.async.shared::cluster.mbarrier::complete_tx::bytes.v4.b32 [%0], {%1,%2,%3,%4}, [%5];"
                 ::"r"(a), "r"(x), "r"(y), "r"(z), "r"(w), "r"(bar) : "memory");
}
__device__ __forceinline__ void st_async64(uint32_t a, uint32_t x, uint32_t y, uint32_t bar) {
    asm volatile("st.async.shared::cluster.mbarrier::complete_tx::bytes.v2.b32 [%0], {%1,%2}, [%3];"
                 ::"r"(a), "r"(x), "r"(y), "r"(bar) : "memory");
}
__device__ __forceinline__ void mma16816(float (&c)[4], const uint4& a, uint32_t b0, uint32_t b1) {
    asm volatile("mma.sync.aligned.m16n8k16.row.col.f32.bf16.bf16.f32 {%0,%1,%2,%3}, {%4,%5,%6,%7}, {%8,%9}, {%0,%1,%2,%3};"
                 : "+f"(c[0]), "+f"(c[1]), "+f"(c[2]), "+f"(c[3])
                 : "r"(a.x), "r"(a.y), "r"(a.z), "r"(a.w), "r"(b0), "r"(b1));
}
__device__ __forceinline__ uint4 lds128(uint32_t a) {
    uint4 v;
    asm volatile("ld.shared.v4.u32 {%0,%1,%2,%3}, [%4];" : "=r"(v.x), "=r"(v.y), "=r"(v.z), "=r"(v.w) : "r"(a) : "memory");
    return v;
}
__device__ __forceinline__ float4 lds128f(uint32_t a) {
    float4 v;
    asm volatile("ld.shared.v4.f32 {%0,%1,%2,%3}, [%4];" : "=f"(v.x), "=f"(v.y), "=f"(v.z), "=f"(v.w) : "r"(a) : "memory");
    return v;
}
__device__ __forceinline__ float2 lds64f(uint32_t a) {
    float2 v;
    asm volatile("ld.shared.v2.f32 {%0,%1}, [%2];" : "=f"(v.x), "=f"(v.y) : "r"(a) : "memory");
    return v;
}
__device__ __forceinline__ uint2 lds64(uint32_t a) {
    uint2 v;
    asm volatile("ld.shared.v2.u32 {%0,%1}, [%2];" : "=r"(v.x), "=r"(v.y) : "r"(a) : "memory");
    return v;
}
__device__ __forceinline__ uint32_t lds32(uint32_t a) {
    uint32_t v;
    asm volatile("ld.shared.u32 %0, [%1];" : "=r"(v) : "r"(a) : "memory");
    return v;
}
__device__ __forceinline__ float lds32f(uint32_t a) { return __uint_as_float(lds32(a)); }
__device__ __forceinline__ void sts128f(uint32_t a, float x, float y, float z, float w) {
    asm volatile("st.shared.v4.f32 [%0], {%1,%2,%3,%4};" ::"r"(a), "f"(x), "f"(y), "f"(z), "f"(w) : "memory");
}
__device__ __forceinline__ void sts32(uint32_t a, uint32_t v) {
    asm volatile("st.shared.u32 [%0], %1;" ::"r"(a), "r"(v) : "memory");
}
__device__ __forceinline__ void sts16(uint32_t a, unsigned short v) {
    asm volatile("st.shared.u16 [%0], %1;" ::"r"(a), "h"(v) : "memory");
}
__device__ __forceinline__ uint4 ldsm4t(uint32_t a) {
    uint4 v;
    asm volatile("ldmatrix.sync.aligned.m8n8.x4.trans.shared.b16 {%0,%1,%2,%3}, [%4];"
                 : "=r"(v.x), "=r"(v.y), "=r"(v.z), "=r"(v.w) : "r"(a) : "memory");
    return v;
}
__device__ __forceinline__ uint32_t pack_bf16(float lo, float hi) {
    uint32_t r;
    asm("cvt.rn.bf16x2.f32 %0, %1, %2;" : "=r"(r) : "f"(hi), "f"(lo));
    return r;
}
__device__ __forceinline__ float round_bf16(float v) { return __uint_as_float(pack_bf16(0.f, v) & 0xFFFF0000u); }
__device__ __forceinline__ float exp_score(float d) {
    float y;
    asm("ex2.approx.ftz.f32 %0, %1;" : "=f"(y) : "f"(d * (0.0625f * 1.4426950408889634f)));
    return y;
}
__device__ __forceinline__ uint32_t fu(float v) { return __float_as_uint(v); }

__device__ __forceinline__ float acc_value(unsigned long long tot) {
    return fmaf((float)(int)(uint32_t)(tot >> 32), 0x1p-24f, (float)((uint32_t)tot >> 10) * 0x1p-46f);
}
__device__ __noinline__ void finish_with_side(unsigned long long tot, unsigned long long* acc_p, __nv_bfloat16* out_p) {
    if ((tot & 31ull) != 16ull) return;
    __threadfence();
    const float side = atomicExch(&g_side[acc_p - g_acc], 0.0f);
    *out_p = __float2bfloat16(acc_value(tot) + side);
    *acc_p = 0ull;
}
__device__ __noinline__ void accumulate_slow(float sum, unsigned long long* acc_p, __nv_bfloat16* out_p) {
    atomicAdd(&g_side[acc_p - g_acc], sum);
    __threadfence();
    finish_with_side(atomicAdd(acc_p, 33ull) + 33ull, acc_p, out_p);
}

__global__ void __launch_bounds__(NTHREADS, 2)
decode_kernel(const __nv_bfloat16* __restrict__ x, const __nv_bfloat16* __restrict__ kc,
              const __nv_bfloat16* __restrict__ wq, __nv_bfloat16* __restrict__ out,
              unsigned long long* __restrict__ acc, const uint32_t zero,
              const __grid_constant__ CUtensorMap wq_map, const __grid_constant__ CUtensorMap wo_map,
              const __grid_constant__ CUtensorMap v_map) {
    asm volatile("prefetch.global.L2 [%0];" ::"l"((const char*)wq + (blockIdx.x * 224 + min(threadIdx.x, 223u)) * 128));

    extern __shared__ __align__(1024) unsigned char smem[];
    const uint32_t sb = (uint32_t)__cvta_generic_to_shared(smem);
    const int warp = threadIdx.x >> 5, lane = threadIdx.x & 31;
    const int cta = blockIdx.x;
    const int gk = cta >> 4, r = cta & 15, b = r >> 2, s = r & 3;
    const bool proj = r < 14;
    const int c = r - 7 * (r >= 7);
    const uint32_t qfull = sb + OFF_BAR, kfull = qfull + 8, vfull = kfull + 64, ofull = vfull + 128, empty = ofull + 32;
    const uint32_t qbar = empty + 14 * 8, stbar = qbar + 8, obar = qbar + 16, hbar = qbar + 24, done = qbar + 56;
    uint32_t spins = 0;

    if (warp == 0) {
        const bool leader = elect_one();
        if (leader) {
            mbar_init(qfull, 1);
            mbar_expect_tx(qfull, 28672 + 3584);
            tma2d(sb, &wq_map, (cta >> 1) * 64, (cta & 1) * 224, qfull);
            fence_mbar_init();
        }
        uint32_t smid;
        asm volatile("mov.u32 %0, %%smid;" : "=r"(smid));
        const uint32_t gpc = smid < 64 ? (smid >> 1) & 7 : 1 + ((smid - 64) >> 1) % 7;
        uint32_t due = now_ns() + T_K0 - (gk == 7 ? T_LEAD : (gpc - 4u < 3u ? T_FAR : 0));
        __syncwarp();
        cluster_arrive();
        cluster_wait();
        if (leader) {
            if (proj) bulk_g2s_mc(sb + OFF_OB + r * 256, (const char*)x + r * 256, 256, qfull, (uint16_t)0xFFFF);
            int row = (b * 8 + gk) * SK + WIN0 + s * 256;
            const char* kp = (const char*)kc + (size_t)row * 512;
            uint32_t bar = kfull, dst = sb + 2 * SLOT;
#pragma unroll 1
            for (int i = 0; i < 8; i++) {
                mbar_expect_tx(bar, 16384);
                if (i >= 4) mbar_wait(empty + 8 * (i - 4));
                pace(due, i < MIN_K ? qfull : bar - 8 * MIN_K);
                bulk_g2s(dst, kp, 16384, bar);
                if (i == 1) {
                    asm volatile("prefetch.tensormap [%0];" ::"l"(&v_map) : "memory");
                    asm volatile("prefetch.tensormap [%0];" ::"l"(&wo_map) : "memory");
                }
                due += T_K;
                kp += 16384;
                bar += 8;
                dst = (i == 3) ? sb : dst + SLOT;
            }
#pragma unroll 1
            for (int k = 0; k < 16; k++) {
                mbar_expect_tx(bar, 8192);
                mbar_wait(empty + 8 * (4 + (k >> 1)));
                const int d = k - MIN_V;
                pace(due, vfull + 8 * (d < 0 ? (d >> 1) : d));
                tma3d(dst, &v_map, row, bar);
                due += k < 12 ? T_V : T_V2;
                row += 16;
                bar += 8;
                dst = (k == 3) ? sb : dst + 8192;
            }
            if (proj) {
                due += T_GAP;
                mbar_wait(empty + 8 * 12);
                mbar_wait(empty + 8 * 13);
#pragma unroll 1
                for (int n = 0; n < 4; n++) {
                    mbar_expect_tx(bar, 8192);
                    if (gk != 7) mbar_wait(bar - 8 * MAX_O);
                    pace(due, bar - 8);
                    tma4d(sb + n * 8192, &wo_map, c * 64, (n + c) & 3, (2 * gk + (r >= 7)) * 2, bar);
                    due += T_O;
                    bar += 8;
                }
            }
            mbar_wait(done);
            if (spins >= SPIN_LIMIT) __trap();
        }
        return;
    }

    const int w = warp - 1, j = threadIdx.x - 32;
    const int g = lane >> 2, t = lane & 3;

    if (w < 7) {
        cluster_arrive();
        cluster_wait();
        const uint32_t qa = sb + (w * 32 + (lane >> 4) * 8 + (lane & 7)) * 128;
        const uint32_t xa = sb + OFF_OB + (g & 3) * 896 + (cta & 1) * 448 + w * 64 + t * 4;
        mbar_wait(qfull);
        const uint32_t x0 = lds32(xa), x1 = lds32(xa + 16), x2 = lds32(xa + 32), x3 = lds32(xa + 48);
        float cq[4][4];
#pragma unroll
        for (int m = 0; m < 4; m++) {
            const uint32_t a = qa + (((2 * m + ((lane >> 3) & 1)) ^ (lane & 7)) << 4);
            const uint4 f0 = ldsm4t(a), f1 = ldsm4t(a + 2048);
            cq[m][0] = cq[m][1] = cq[m][2] = cq[m][3] = 0.f;
            mma16816(cq[m], f0, x0, x1);
            mma16816(cq[m], f1, x2, x3);
        }
        slot_release(empty + 8 * (w >> 2), fu(cq[0][0]) ^ fu(cq[1][0]) ^ fu(cq[2][0]) ^ fu(cq[3][0]), zero, lane);
        const int hf = t >> 1;
        const uint32_t qr = sb + OFF_QRED + w * 1024 + (t & 1) * 512 + hf * 128 + g * 16;
        sts128f(qr, hf ? cq[0][2] : cq[0][0], hf ? cq[1][2] : cq[1][0], hf ? cq[2][2] : cq[2][0], hf ? cq[3][2] : cq[3][0]);
        sts128f(qr + 256, hf ? cq[0][3] : cq[0][1], hf ? cq[1][3] : cq[1][1], hf ? cq[2][3] : cq[2][1], hf ? cq[3][3] : cq[3][1]);
    } else {
        if (lane == 0) {
#pragma unroll
            for (int i = 0; i < 28; i++) mbar_init(kfull + 8 * i, 1);
#pragma unroll
            for (int i = 0; i < 14; i++) mbar_init(empty + 8 * i, i == 1 ? 3 : (i < 10 ? 4 : 8));
#pragma unroll
            for (int i = 0; i < 7; i++) mbar_init(qbar + 8 * i, 1);
            mbar_init(done, 8);
            mbar_expect_tx(qbar, 4096);
            mbar_expect_tx(stbar, 64);
            mbar_expect_tx(obar, 2048);
#pragma unroll
            for (int i = 0; i < 4; i++) mbar_expect_tx(hbar + 8 * i, 512);
            fence_mbar_init();
        }
        __syncwarp();
        cluster_arrive();
        cluster_wait();
    }
    bar_compute();
    {
        const int pk = j >> 2;
        const uint32_t ra = sb + OFF_QRED + pk * 16;
        float4 a = lds128f(ra);
#pragma unroll
        for (int ww = 1; ww < 7; ww++) {
            const float4 v = lds128f(ra + ww * 1024);
            a.x += v.x; a.y += v.y; a.z += v.z; a.w += v.w;
        }
        const uint32_t dst = (pk >> 4) * 4 + (j & 3);
        st_async128(mapa(sb + OFF_QBUF + (r & 1) * 2048 + (r >> 1) * 256 + (pk & 15) * 16, dst),
                    fu(a.x), fu(a.y), fu(a.z), fu(a.w), mapa(qbar, dst));
        mbar_wait(qbar);
        const uint32_t qb = sb + OFF_QBUF + (j >> 5) * 256 + (j & 7) * 32 + ((j >> 3) & 3) * 4;
        const float q0 = lds32f(qb) + lds32f(qb + 2048), q1 = lds32f(qb + 16) + lds32f(qb + 2064);
        sts32(sb + OFF_QS + ((j >> 5) & 3) * 256 + (j & 1) * 128 + (j >> 7) * 64 + ((j >> 2) & 3) * 16 + ((j >> 4) & 1) * 8 + ((j >> 1) & 1) * 4,
              pack_bf16(q0, q1));
    }
    bar_compute();

    float s0 = 0.f, s1 = 0.f;
    {
        uint2 qf[8];
        const uint32_t qa = sb + OFF_QS + (g >> 2) * 128 + (g & 1) * 64 + t * 16;
        const uint32_t qx = ((g >> 1) & 1) * 8;
#pragma unroll
        for (int i = 0; i < 8; i++) qf[i] = lds64(qa + (i >> 1) * 256 + (((i & 1) * 8) ^ qx));
        const uint32_t kx = (g & 1) * 64;
        const uint32_t krow = sb + ((w & 3) * 8 + g) * 512 + t * 16;
        const int src = (lane & 28) + (g & 1);
#pragma unroll 1
        for (int k = 0; k < 4; k++) {
            const int ch = 2 * k + (w >> 2);
            const uint32_t ka = krow + (ch >= 4 ? ch - 4 : ch + 2) * SLOT;
            mbar_wait(kfull + 8 * ch);
            float a0[4] = {0.f, 0.f, 0.f, 0.f}, a1[4] = {0.f, 0.f, 0.f, 0.f};
#pragma unroll
            for (int i = 0; i < 8; i += 2) {
                const uint4 r0 = lds128(ka + ((i * 64) ^ kx)), r1 = lds128(ka + (((i + 1) * 64) ^ kx));
                mma16816(a0, r0, qf[i].x, qf[i].y);
                mma16816(a1, r1, qf[i + 1].x, qf[i + 1].y);
            }
            const float e0 = __shfl_sync(0xffffffffu, a0[0] + a1[0], src) + __shfl_sync(0xffffffffu, a0[2] + a1[2], src + 2);
            const float e1 = __shfl_sync(0xffffffffu, a0[1] + a1[1], src) + __shfl_sync(0xffffffffu, a0[3] + a1[3], src + 2);
            slot_release(empty + 8 * (2 + ch), fu(e0), zero, lane);
            if (t == k) { s0 = e0; s1 = e1; }
        }
    }
    float Mown;
    {
        s0 = round_bf16(s0);
        s1 = round_bf16(s1);
        float m0 = s0, m1 = s1;
#pragma unroll
        for (int o = 16; o > 0; o >>= 1) {
            m0 = fmaxf(m0, __shfl_xor_sync(0xffffffffu, m0, o));
            m1 = fmaxf(m1, __shfl_xor_sync(0xffffffffu, m1, o));
        }
        if (lane < 2) sts32(sb + OFF_WST + (w * 2 + lane) * 4, fu(lane ? m1 : m0));
        bar_compute();
        const float4 u0 = lds128f(sb + OFF_WST), u1 = lds128f(sb + OFF_WST + 16), u2 = lds128f(sb + OFF_WST + 32), u3 = lds128f(sb + OFF_WST + 48);
        const float M0 = fmaxf(fmaxf(fmaxf(u0.x, u0.z), fmaxf(u1.x, u1.z)), fmaxf(fmaxf(u2.x, u2.z), fmaxf(u3.x, u3.z)));
        const float M1 = fmaxf(fmaxf(fmaxf(u0.y, u0.w), fmaxf(u1.y, u1.w)), fmaxf(fmaxf(u2.y, u2.w), fmaxf(u3.y, u3.w)));
        Mown = (t & 1) ? M1 : M0;
        const uint32_t p = pack_bf16(exp_score(s0 - M0), exp_score(s1 - M1));
        const uint32_t pa = sb + OFF_PS + (4 * t + (w >> 1)) * 64 + (g >> 1) * 8 + (w & 1) * 4 + (g & 1) * 2;
        sts16(pa, (unsigned short)(p & 0xFFFFu));
        sts16(pa + 32, (unsigned short)(p >> 16));
        float l0 = __uint_as_float(p << 16), l1 = __uint_as_float(p & 0xFFFF0000u);
#pragma unroll
        for (int o = 16; o > 0; o >>= 1) {
            l0 += __shfl_xor_sync(0xffffffffu, l0, o);
            l1 += __shfl_xor_sync(0xffffffffu, l1, o);
        }
        if (lane < 2) sts32(sb + OFF_WST + 64 + (w * 2 + lane) * 4, fu(lane ? l1 : l0));
        bar_compute();
        if (j < 4) {
            const float4 v0 = lds128f(sb + OFF_WST + 64), v1 = lds128f(sb + OFF_WST + 80), v2 = lds128f(sb + OFF_WST + 96), v3 = lds128f(sb + OFF_WST + 112);
            const float L0 = ((v0.x + v0.z) + (v1.x + v1.z)) + ((v2.x + v2.z) + (v3.x + v3.z));
            const float L1 = ((v0.y + v0.w) + (v1.y + v1.w)) + ((v2.y + v2.w) + (v3.y + v3.w));
            st_async128(mapa(sb + OFF_WST + 128 + s * 16, b * 4 + j), fu(M0), fu(L0), fu(M1), fu(L1), mapa(stbar, b * 4 + j));
        }
    }

    const uint32_t h1_dst = pin(mapa(sb + OFF_HOP + r * 128 + (t >> 1) * 64 + g * 8, (t & 1) * 8 + w));
    const uint32_t h1_bar = pin(mapa(hbar + 8 * b, (t & 1) * 8 + w));
    const uint32_t h2_grp = (w >> 2) * 4 + (lane >> 3);
    const uint32_t h2_rank = h2_grp < 7 ? (r >> 3) * 7 + h2_grp : 14 + (r >> 3);
    const uint32_t h2_dst = pin(mapa(sb + OFF_OB + (w & 3) * OB_STRIDE + ((r - h2_grp) & 3) * 128 + ((r >> 2) & 1) * 64 +
                                     (lane & 3) * 16 + ((lane >> 2) & 1) * 8, h2_rank));
    const uint32_t h2_bar = pin(mapa(obar, h2_rank));
    const uint32_t h2_src = pin(sb + OFF_HOP + (w & 3) * 512 + (lane & 7) * 16);
    const uint32_t h2_wait = pin(hbar + 8 * (w & 3));
    const uint32_t bars = pin(obar);
    const uint32_t wo_src = pin(sb + (((lane >> 3) & 1) * 16 + (lane >> 4) * 8 + (lane & 7)) * 128 + ((w ^ (lane & 7)) << 4));
    const uint32_t ob_src = pin(sb + OFF_OB + (g & 3) * OB_STRIDE + (g >> 2) * 64 + t * 16);
    unsigned long long* acc_p = pin_ptr(acc + (c & 3) * 2048 + 512 + (c >> 2) * 512 + (j >> 4) * 32 + (j & 15));
    __nv_bfloat16* out_p = pin_ptr(out + (g & 3) * 448 + c * 64 + w * 8 + 2 * t + (g >> 2));
    const uint32_t k_one = pin(zero + 1u);
    const bool t_hi = pin(t >> 1) != 0, g_hi = pin(g >> 2) != 0, proj_on = pin(proj ? 1u : 0u) != 0;

    float acc0[4] = {0.f, 0.f, 0.f, 0.f}, acc1[4] = {0.f, 0.f, 0.f, 0.f};
    float wgt;
    {
        const uint32_t va0 = pin(sb + (w >> 1) * 2048 + ((lane >> 4) * 8 + (lane & 7)) * 128 + ((((w & 1) * 4 + ((lane >> 3) & 1)) ^ (lane & 7)) << 4));
        const uint32_t va1 = pin(va0 ^ 32);
        const uint32_t pa = pin(sb + OFF_PS + ((g >> 1) & 1) * 32 + t * 8);
        const uint32_t vb = bars - (obar - vfull);
#pragma unroll 1
        for (int k = 0; k < 8; k += 2) {
            const uint32_t so = (k < 4 ? k + 8 : k - 4) * 8192;
            const uint2 p0 = lds64(pa + k * 64), p1 = lds64(pa + k * 64 + 64);
            mbar_wait(vb + 8 * k);
            const uint4 f0 = ldsm4t(va0 + so), f1 = ldsm4t(va1 + so);
            mma16816(acc0, f0, p0.x, p0.y);
            mma16816(acc1, f1, p0.x, p0.y);
            mbar_wait(vb + 8 * k + 8);
            const uint4 f2 = ldsm4t(va0 + so + 8192), f3 = ldsm4t(va1 + so + 8192);
            mma16816(acc0, f2, p1.x, p1.y);
            mma16816(acc1, f3, p1.x, p1.y);
            slot_release(empty + 8 * (10 + (k >> 1)), fu(acc0[0]) ^ fu(acc1[0]), zero, lane);
        }
        uint2 pw[8];
#pragma unroll
        for (int k = 8; k < 16; k++) pw[k - 8] = lds64(pa + k * 64);
        {
            mbar_wait(stbar);
            const uint32_t sa = sb + OFF_WST + 128 + (t & 1) * 8;
            const float2 z0 = lds64f(sa), z1 = lds64f(sa + 16), z2 = lds64f(sa + 32), z3 = lds64f(sa + 48);
            const float mx = fmaxf(fmaxf(z0.x, z1.x), fmaxf(z2.x, z3.x));
            const float W = (exp_score(z0.x - mx) * z0.y + exp_score(z1.x - mx) * z1.y) +
                            (exp_score(z2.x - mx) * z2.y + exp_score(z3.x - mx) * z3.y);
            wgt = __uint_as_float(pin(fu(__fdividef(exp_score(Mown - mx), W))));
        }
        uint4 f0, f1;
#pragma unroll
        for (int k = 8; k < 16; k++) {
            mbar_wait_fast(vb + 8 * k);
            const uint4 n0 = ldsm4t(va0 + (k - 4) * 8192), n1 = ldsm4t(va1 + (k - 4) * 8192);
            if (k > 8) {
                mma16816(acc0, f0, pw[k - 9].x, pw[k - 9].y);
                mma16816(acc1, f1, pw[k - 9].x, pw[k - 9].y);
            }
            f0 = n0; f1 = n1;
        }
        mma16816(acc0, f0, pw[7].x, pw[7].y);
        mma16816(acc1, f1, pw[7].x, pw[7].y);
    }
    st_async64(h1_dst, fu((t_hi ? acc1[0] : acc0[0]) * wgt), fu((t_hi ? acc1[2] : acc0[2]) * wgt), h1_bar);
    {
        mbar_wait_fast(h2_wait);
        const float4 v0 = lds128f(h2_src), v1 = lds128f(h2_src + 128), v2 = lds128f(h2_src + 256), v3 = lds128f(h2_src + 384);
        st_async64(h2_dst, pack_bf16((v0.x + v1.x) + (v2.x + v3.x), (v0.z + v1.z) + (v2.z + v3.z)),
                   pack_bf16((v0.y + v1.y) + (v2.y + v3.y), (v0.w + v1.w) + (v2.w + v3.w)), h2_bar);
    }
    if (!proj_on) {
        mbar_wait_fast(bars);
        slot_release(bars + (done - obar), 0u, 0u, lane);
        return;
    }
    float sum;
    {
        const uint32_t ob = bars - (obar - ofull);
        float x0[4] = {0.f, 0.f, 0.f, 0.f}, x1[4] = {0.f, 0.f, 0.f, 0.f}, y0[4] = {0.f, 0.f, 0.f, 0.f}, y1[4] = {0.f, 0.f, 0.f, 0.f};
        uint4 bp[4], bq[4], oa[4];
#pragma unroll
        for (int n = 0; n < 3; n++) {
            mbar_wait_fast(ob + 8 * n);
            bp[n] = ldsm4t(wo_src + n * 8192);
            bq[n] = ldsm4t(wo_src + n * 8192 + 4096);
        }
        mbar_wait_fast(bars);
#pragma unroll
        for (int n = 0; n < 4; n++) oa[n] = lds128(ob_src + n * 128);
#pragma unroll
        for (int n = 0; n < 4; n++) {
            if (n == 3) {
                mbar_wait_fast(ob + 24);
                bp[3] = ldsm4t(wo_src + 3 * 8192);
                bq[3] = ldsm4t(wo_src + 3 * 8192 + 4096);
            }
            mma16816(x0, oa[n], bp[n].x, bp[n].y);
            mma16816(y0, oa[n], bp[n].z, bp[n].w);
            mma16816(x1, oa[n], bq[n].x, bq[n].y);
            mma16816(y1, oa[n], bq[n].z, bq[n].w);
        }
        float keep = x0[0] + y0[2], send = x0[1] + y0[3];
        if (g_hi) { send = x1[0] + y1[2]; keep = x1[1] + y1[3]; }
        sum = keep + __shfl_xor_sync(0xffffffffu, send, 16);
    }
    const uint32_t bits = fu(sum);
    const uint32_t sh = 129u - ((bits >> 23) & 0xFFu);
    const uint32_t smant = (((bits << 3) & 0x3FFFFF8u) | 0x4000000u) ^ (uint32_t)((int)bits >> 31);
    long long fx;
    asm("shr.s64 %0, %1, %2;" : "=l"(fx) : "l"((long long)((unsigned long long)smant << 32)), "r"(sh));
    const unsigned long long inc = ((unsigned long long)fx & 0xFFFFFFFF00000000ull) | (((uint32_t)fx & ~0x3FFu) | k_one);
    const bool fast = __any_sync(0xffffffffu, fabsf(sum) >= 0x1p-22f) && fabsf(sum) < 8.0f;
    unsigned long long tot = 0ull;
    asm volatile("{\n.reg .pred p;\nsetp.ne.u32 p, %3, 0;\n@p atom.relaxed.gpu.global.add.u64 %0, [%1], %2;\n}"
                 : "+l"(tot) : "l"(acc_p), "l"(inc), "r"((uint32_t)fast) : "memory");
    slot_release(bars + (done - obar), 0u, 0u, lane);
    if (!fast) { accumulate_slow(sum, acc_p, out_p); return; }
    tot += inc;
    const uint32_t cnt = (uint32_t)tot & 0x3FFu;
    asm volatile("{\n.reg .pred p;\nsetp.eq.u32 p, %3, 16;\n@p st.global.u16 [%0], %1;\n@p st.global.u64 [%2], 0;\n}"
                 ::"l"(out_p), "h"(__bfloat16_as_ushort(__float2bfloat16(acc_value(tot)))), "l"(acc_p), "r"(cnt) : "memory");
    if (cnt > 16u) finish_with_side(tot, acc_p, out_p);
}

typedef CUresult (*EncodeFn)(CUtensorMap*, CUtensorMapDataType, cuuint32_t, void*, const cuuint64_t*, const cuuint64_t*,
                             const cuuint32_t*, const cuuint32_t*, CUtensorMapInterleave, CUtensorMapSwizzle,
                             CUtensorMapL2promotion, CUtensorMapFloatOOBfill);

}

extern "C" void kernel_launch(void* const* d_in, const int* in_sizes, int n_in, void* d_out, int out_size) {
    (void)in_sizes; (void)n_in; (void)out_size;
    static EncodeFn encode = nullptr;
    static void* acc = nullptr;
    if (!encode) {
        cudaDriverEntryPointQueryResult qr;
        cudaGetDriverEntryPoint("cuTensorMapEncodeTiled", (void**)&encode, cudaEnableDefault, &qr);
        cudaGetSymbolAddress(&acc, g_acc);
        cudaFuncSetAttribute(decode_kernel, cudaFuncAttributeMaxDynamicSharedMemorySize, SMEM_BYTES);
        cudaFuncSetAttribute(decode_kernel, cudaFuncAttributeNonPortableClusterSizeAllowed, 1);
    }
    const cuuint32_t estr[4] = {1, 1, 1, 1};
    CUtensorMap wq_map, wo_map, v_map;
    {
        const cuuint64_t dim[2] = {4096, 448}, str[1] = {8192};
        const cuuint32_t box[2] = {64, 224};
        encode(&wq_map, CU_TENSOR_MAP_DATA_TYPE_BFLOAT16, 2, d_in[3], dim, str, box, estr, CU_TENSOR_MAP_INTERLEAVE_NONE,
               CU_TENSOR_MAP_SWIZZLE_128B, CU_TENSOR_MAP_L2_PROMOTION_NONE, CU_TENSOR_MAP_FLOAT_OOB_FILL_NONE);
    }
    {
        const cuuint64_t dim[4] = {448, 32, 4, 32}, str[3] = {896, 896 * 32, 896 * 128};
        const cuuint32_t box[4] = {64, 32, 1, 2};
        encode(&wo_map, CU_TENSOR_MAP_DATA_TYPE_BFLOAT16, 4, d_in[4], dim, str, box, estr, CU_TENSOR_MAP_INTERLEAVE_NONE,
               CU_TENSOR_MAP_SWIZZLE_128B, CU_TENSOR_MAP_L2_PROMOTION_NONE, CU_TENSOR_MAP_FLOAT_OOB_FILL_NONE);
    }
    {
        const cuuint64_t dim[3] = {64, 4ull * 8 * SK, 4}, str[2] = {512, 128};
        const cuuint32_t box[3] = {64, 16, 4};
        encode(&v_map, CU_TENSOR_MAP_DATA_TYPE_BFLOAT16, 3, d_in[2], dim, str, box, estr, CU_TENSOR_MAP_INTERLEAVE_NONE,
               CU_TENSOR_MAP_SWIZZLE_128B, CU_TENSOR_MAP_L2_PROMOTION_NONE, CU_TENSOR_MAP_FLOAT_OOB_FILL_NONE);
    }
    cudaLaunchConfig_t cfg = {};
    cfg.gridDim = dim3(128);
    cfg.blockDim = dim3(NTHREADS);
    cfg.dynamicSmemBytes = SMEM_BYTES;
    cfg.stream = cudaStreamPerThread;
    cudaLaunchAttribute attr[2];
    attr[0].id = cudaLaunchAttributeClusterDimension;
    attr[0].val.clusterDim.x = 16; attr[0].val.clusterDim.y = 1; attr[0].val.clusterDim.z = 1;
    attr[1].id = cudaLaunchAttributeClusterSchedulingPolicyPreference;
    attr[1].val.clusterSchedulingPolicyPreference = cudaClusterSchedulingPolicyLoadBalancing;
    cfg.attrs = attr;
    cfg.numAttrs = 2;
    cudaLaunchKernelEx(&cfg, decode_kernel, (const __nv_bfloat16*)d_in[0], (const __nv_bfloat16*)d_in[1],
                       (const __nv_bfloat16*)d_in[3], (__nv_bfloat16*)d_out, (unsigned long long*)acc, 0u,
                       wq_map, wo_map, v_map);
}
```

```cpp
#include <cuda_runtime.h>
#include <cuda_bf16.h>
#include <cuda.h>
#include <stdint.h>

namespace {

constexpr int SK = 4096, WIN0 = 3072;
constexpr int SLOT = 16384;
constexpr int OFF_QBUF = 6 * SLOT;
constexpr int OFF_QS   = OFF_QBUF + 4096;
constexpr int OB_STRIDE = 576;
constexpr int OFF_OB   = OFF_QS + 1024;
constexpr int OFF_HOP  = OFF_OB + 4 * OB_STRIDE;
constexpr int OFF_QRED = OFF_HOP + 2048;
constexpr int OFF_PS   = OFF_QRED;
constexpr int OFF_WST  = OFF_QRED + 7 * 1024;
constexpr int OFF_BAR  = OFF_WST + 192;
constexpr int SMEM_BYTES = OFF_BAR + 416;
static_assert(SMEM_BYTES <= 115712, "two CTAs must fit on one SM");
constexpr int NTHREADS = 288;
constexpr int SPIN_LIMIT = 1 << 20;

constexpr int T_K0   = 330;
constexpr int T_K    = 670;
constexpr int T_V    = 345;
constexpr int T_V2   = 300;
constexpr int T_GAP  = 70;
constexpr int T_O    = 280;
constexpr int T_LEAD = 1600;
constexpr int T_FAR  = 150;
constexpr int MIN_K = 2, MIN_V = 4;
constexpr int MAX_O = 6;

constexpr int ACC_WORDS = 8192;
__device__ __align__(32768) unsigned long long g_acc[ACC_WORDS];
__device__ float g_side[ACC_WORDS];

__device__ __forceinline__ void mbar_init(uint32_t bar, uint32_t cnt) {
    asm volatile("mbarrier.init.shared::cta.b64 [%0], %1;" ::"r"(bar), "r"(cnt) : "memory");
}
__device__ __forceinline__ void mbar_expect_tx(uint32_t bar, uint32_t bytes) {
    asm volatile("mbarrier.arrive.expect_tx.shared::cta.b64 _, [%0], %1;" ::"r"(bar), "r"(bytes) : "memory");
}
__device__ __forceinline__ void slot_release(uint32_t bar, uint32_t dep, uint32_t zero, int lane) {
    if (lane == 0) asm volatile("mbarrier.arrive.shared::cta.b64 _, [%0];" ::"r"(bar + (dep & zero)) : "memory");
}
__device__ __forceinline__ void mbar_wait_n(uint32_t bar, uint32_t& n) {
    asm volatile("{\n.reg .pred p, q;\n"
                 "WAIT_LOOP:\n"
                 "mbarrier.try_wait.parity.shared::cta.b64 p, [%1], 0;\n"
                 "add.u32 %0, %0, 1;\n"
                 "setp.lt.and.u32 q, %0, %2, !p;\n"
                 "@q bra.uni WAIT_LOOP;\n}"
                 : "+r"(n) : "r"(bar), "n"(SPIN_LIMIT) : "memory");
}
#define mbar_wait(bar) mbar_wait_n(bar, spins)
__device__ __forceinline__ void mbar_wait_fast(uint32_t bar) {
    asm volatile("{\n.reg .pred p;\nWAIT_LOOP:\nmbarrier.try_wait.parity.shared::cta.b64 p, [%0], 0;\n@!p bra.uni WAIT_LOOP;\n}"
                 ::"r"(bar) : "memory");
}
__device__ __forceinline__ uint32_t now_ns() {
    uint32_t t;
    asm volatile("mov.u32 %0, %%globaltimer_lo;" : "=r"(t)::"memory");
    return t;
}
__device__ __forceinline__ void pace(uint32_t due, uint32_t bar) {
    while ((int)(now_ns() - due) < 0) {
        uint32_t ok;
        asm volatile("{\n.reg .pred p;\nmbarrier.test_wait.parity.shared::cta.b64 p, [%1], 0;\nselp.u32 %0, 1, 0, p;\n}"
                     : "=r"(ok) : "r"(bar) : "memory");
        if (ok) break;
    }
}
__device__ __forceinline__ void bulk_g2s(uint32_t dst, const void* src, uint32_t bytes, uint32_t bar) {
    asm volatile("cp.async.bulk.shared::cluster.global.mbarrier::complete_tx::bytes [%0], [%1], %2, [%3];"
                 ::"r"(dst), "l"(src), "r"(bytes), "r"(bar) : "memory");
}
__device__ __forceinline__ void bulk_g2s_mc(uint32_t dst, const void* src, uint32_t bytes, uint32_t bar, uint16_t mask) {
    asm volatile("cp.async.bulk.shared::cluster.global.mbarrier::complete_tx::bytes.multicast::cluster [%0], [%1], %2, [%3], %4;"
                 ::"r"(dst), "l"(src), "r"(bytes), "r"(bar), "h"(mask) : "memory");
}
__device__ __forceinline__ void tma2d(uint32_t dst, const CUtensorMap* tm, int c0, int c1, uint32_t bar) {
    asm volatile("cp.async.bulk.tensor.2d.shared::cluster.global.mbarrier::complete_tx::bytes [%0], [%1, {%3, %4}], [%2];"
                 ::"r"(dst), "l"(tm), "r"(bar), "r"(c0), "r"(c1) : "memory");
}
__device__ __forceinline__ void tma3d(uint32_t dst, const CUtensorMap* tm, int c1, uint32_t bar) {
    asm volatile("cp.async.bulk.tensor.3d.shared::cluster.global.mbarrier::complete_tx::bytes [%0], [%1, {%3, %4, %3}], [%2];"
                 ::"r"(dst), "l"(tm), "r"(bar), "r"(0), "r"(c1) : "memory");
}
__device__ __forceinline__ void tma4d(uint32_t dst, const CUtensorMap* tm, int c0, int c2, int c3, uint32_t bar) {
    asm volatile("cp.async.bulk.tensor.4d.shared::cluster.global.mbarrier::complete_tx::bytes [%0], [%1, {%3, %4, %5, %6}], [%2];"
                 ::"r"(dst), "l"(tm), "r"(bar), "r"(c0), "r"(0), "r"(c2), "r"(c3) : "memory");
}
__device__ __forceinline__ uint32_t pin(uint32_t v) {
    uint32_t o;
    asm volatile("shfl.sync.bfly.b32 %0, %1, 0, 0x1f, 0xffffffff;" : "=r"(o) : "r"(v));
    return o;
}
template <typename T> __device__ __forceinline__ T* pin_ptr(T* p) {
    const unsigned long long a = (unsigned long long)p;
    return (T*)(((unsigned long long)pin((uint32_t)(a >> 32)) << 32) | pin((uint32_t)a));
}
__device__ __forceinline__ bool elect_one() {
    uint32_t p;
    asm volatile("{\n.reg .pred P;\nelect.sync _|P, 0xffffffff;\nselp.u32 %0, 1, 0, P;\n}" : "=r"(p));
    return p != 0;
}
__device__ __forceinline__ void bar_compute() { asm volatile("bar.sync 1, 256;" ::: "memory"); }
__device__ __forceinline__ void cluster_arrive() { asm volatile("barrier.cluster.arrive.relaxed.aligned;" ::: "memory"); }
__device__ __forceinline__ void cluster_wait() { asm volatile("barrier.cluster.wait.aligned;" ::: "memory"); }
__device__ __forceinline__ void fence_mbar_init() { asm volatile("fence.mbarrier_init.release.cluster;" ::: "memory"); }
__device__ __forceinline__ uint32_t mapa(uint32_t a, uint32_t rank) {
    uint32_t o;
    asm("mapa.shared::cluster.u32 %0, %1, %2;" : "=r"(o) : "r"(a), "r"(rank));
    return o;
}
__device__ __forceinline__ void st_async128(uint32_t a, uint32_t x, uint32_t y, uint32_t z, uint32_t w, uint32_t bar) {
    asm volatile("st.async.shared::cluster.mbarrier::complete_tx::bytes.v4.b32 [%0], {%1,%2,%3,%4}, [%5];"
                 ::"r"(a), "r"(x), "r"(y), "r"(z), "r"(w), "r"(bar) : "memory");
}
__device__ __forceinline__ void st_async64(uint32_t a, uint32_t x, uint32_t y, uint32_t bar) {
    asm volatile("st.async.shared::cluster.mbarrier::complete_tx::bytes.v2.b32 [%0], {%1,%2}, [%3];"
                 ::"r"(a), "r"(x), "r"(y), "r"(bar) : "memory");
}
__device__ __forceinline__ void mma16816(float (&c)[4], const uint4& a, uint32_t b0, uint32_t b1) {
    asm volatile("mma.sync.aligned.m16n8k16.row.col.f32.bf16.bf16.f32 {%0,%1,%2,%3}, {%4,%5,%6,%7}, {%8,%9}, {%0,%1,%2,%3};"
                 : "+f"(c[0]), "+f"(c[1]), "+f"(c[2]), "+f"(c[3])
                 : "r"(a.x), "r"(a.y), "r"(a.z), "r"(a.w), "r"(b0), "r"(b1));
}
__device__ __forceinline__ uint4 lds128(uint32_t a) {
    uint4 v;
    asm volatile("ld.shared.v4.u32 {%0,%1,%2,%3}, [%4];" : "=r"(v.x), "=r"(v.y), "=r"(v.z), "=r"(v.w) : "r"(a) : "memory");
    return v;
}
__device__ __forceinline__ float4 lds128f(uint32_t a) {
    float4 v;
    asm volatile("ld.shared.v4.f32 {%0,%1,%2,%3}, [%4];" : "=f"(v.x), "=f"(v.y), "=f"(v.z), "=f"(v.w) : "r"(a) : "memory");
    return v;
}
__device__ __forceinline__ float2 lds64f(uint32_t a) {
    float2 v;
    asm volatile("ld.shared.v2.f32 {%0,%1}, [%2];" : "=f"(v.x), "=f"(v.y) : "r"(a) : "memory");
    return v;
}
__device__ __forceinline__ uint2 lds64(uint32_t a) {
    uint2 v;
    asm volatile("ld.shared.v2.u32 {%0,%1}, [%2];" : "=r"(v.x), "=r"(v.y) : "r"(a) : "memory");
    return v;
}
__device__ __forceinline__ uint32_t lds32(uint32_t a) {
    uint32_t v;
    asm volatile("ld.shared.u32 %0, [%1];" : "=r"(v) : "r"(a) : "memory");
    return v;
}
__device__ __forceinline__ float lds32f(uint32_t a) { return __uint_as_float(lds32(a)); }
__device__ __forceinline__ void sts128f(uint32_t a, float x, float y, float z, float w) {
    asm volatile("st.shared.v4.f32 [%0], {%1,%2,%3,%4};" ::"r"(a), "f"(x), "f"(y), "f"(z), "f"(w) : "memory");
}
__device__ __forceinline__ void sts32(uint32_t a, uint32_t v) {
    asm volatile("st.shared.u32 [%0], %1;" ::"r"(a), "r"(v) : "memory");
}
__device__ __forceinline__ void sts16(uint32_t a, unsigned short v) {
    asm volatile("st.shared.u16 [%0], %1;" ::"r"(a), "h"(v) : "memory");
}
__device__ __forceinline__ uint4 ldsm4t(uint32_t a) {
    uint4 v;
    asm volatile("ldmatrix.sync.aligned.m8n8.x4.trans.shared.b16 {%0,%1,%2,%3}, [%4];"
                 : "=r"(v.x), "=r"(v.y), "=r"(v.z), "=r"(v.w) : "r"(a) : "memory");
    return v;
}
__device__ __forceinline__ uint32_t pack_bf16(float lo, float hi) {
    uint32_t r;
    asm("cvt.rn.bf16x2.f32 %0, %1, %2;" : "=r"(r) : "f"(hi), "f"(lo));
    return r;
}
__device__ __forceinline__ float round_bf16(float v) { return __uint_as_float(pack_bf16(0.f, v) & 0xFFFF0000u); }
__device__ __forceinline__ float exp_score(float d) {
    float y;
    asm("ex2.approx.ftz.f32 %0, %1;" : "=f"(y) : "f"(d * (0.0625f * 1.4426950408889634f)));
    return y;
}
__device__ __forceinline__ uint32_t fu(float v) { return __float_as_uint(v); }

__device__ __forceinline__ float acc_value(unsigned long long tot) {
    return fmaf((float)(int)(uint32_t)(tot >> 32), 0x1p-24f, (float)((uint32_t)tot >> 10) * 0x1p-46f);
}
__device__ __noinline__ void finish_with_side(unsigned long long tot, unsigned long long* acc_p, __nv_bfloat16* out_p) {
    if ((tot & 31ull) != 16ull) return;
    __threadfence();
    const float side = atomicExch(&g_side[acc_p - g_acc], 0.0f);
    *out_p = __float2bfloat16(acc_value(tot) + side);
    *acc_p = 0ull;
}
__device__ __noinline__ void accumulate_slow(float sum, unsigned long long* acc_p, __nv_bfloat16* out_p) {
    atomicAdd(&g_side[acc_p - g_acc], sum);
    __threadfence();
    finish_with_side(atomicAdd(acc_p, 33ull) + 33ull, acc_p, out_p);
}

__global__ void __launch_bounds__(NTHREADS, 2)
decode_kernel(const __nv_bfloat16* __restrict__ x, const __nv_bfloat16* __restrict__ kc,
              const __nv_bfloat16* __restrict__ wq, __nv_bfloat16* __restrict__ out,
              unsigned long long* __restrict__ acc, const uint32_t zero,
              const __grid_constant__ CUtensorMap wq_map, const __grid_constant__ CUtensorMap wo_map,
              const __grid_constant__ CUtensorMap v_map) {
    asm volatile("prefetch.global.L2 [%0];" ::"l"((const char*)wq + (blockIdx.x * 224 + min(threadIdx.x, 223u)) * 128));

    extern __shared__ __align__(1024) unsigned char smem[];
    const uint32_t sb = (uint32_t)__cvta_generic_to_shared(smem);
    const int warp = threadIdx.x >> 5, lane = threadIdx.x & 31;
    const int cta = blockIdx.x;
    const int gk = cta >> 4, r = cta & 15, b = r >> 2, s = r & 3;
    const bool proj = r < 14;
    const int c = r - 7 * (r >= 7);
    const uint32_t qfull = sb + OFF_BAR, kfull = qfull + 8, vfull = kfull + 64, ofull = vfull + 128, empty = ofull + 32;
    const uint32_t qbar = empty + 14 * 8, stbar = qbar + 8, obar = qbar + 16, hbar = qbar + 24, done = qbar + 56;
    uint32_t spins = 0;

    if (warp == 0) {
        const bool leader = elect_one();
        if (leader) {
            mbar_init(qfull, 1);
            mbar_expect_tx(qfull, 28672 + 3584);
            tma2d(sb, &wq_map, (cta >> 1) * 64, (cta & 1) * 224, qfull);
            fence_mbar_init();
        }
        uint32_t smid;
        asm volatile("mov.u32 %0, %%smid;" : "=r"(smid));
        const uint32_t gpc = smid < 64 ? (smid >> 1) & 7 : 1 + ((smid - 64) >> 1) % 7;
        uint32_t due = now_ns() + T_K0 - (gk == 7 ? T_LEAD : (gpc - 4u < 3u ? T_FAR : 0));
        __syncwarp();
        cluster_arrive();
        cluster_wait();
        if (leader) {
            if (proj) bulk_g2s_mc(sb + OFF_OB + r * 256, (const char*)x + r * 256, 256, qfull, (uint16_t)0xFFFF);
            int row = (b * 8 + gk) * SK + WIN0 + s * 256;
            const char* kp = (const char*)kc + (size_t)row * 512;
            uint32_t bar = kfull, dst = sb + 2 * SLOT;
#pragma unroll 1
            for (int i = 0; i < 8; i++) {
                mbar_expect_tx(bar, 16384);
                if (i >= 4) mbar_wait(empty + 8 * (i - 4));
                pace(due, i < MIN_K ? qfull : bar - 8 * MIN_K);
                bulk_g2s(dst, kp, 16384, bar);
                if (i == 1) {
                    asm volatile("prefetch.tensormap [%0];" ::"l"(&v_map) : "memory");
                    asm volatile("prefetch.tensormap [%0];" ::"l"(&wo_map) : "memory");
                }
                due += T_K;
                kp += 16384;
                bar += 8;
                dst = (i == 3) ? sb : dst + SLOT;
            }
#pragma unroll 1
            for (int k = 0; k < 16; k++) {
                mbar_expect_tx(bar, 8192);
                mbar_wait(empty + 8 * (4 + (k >> 1)));
                const int d = k - MIN_V;
                pace(due, vfull + 8 * (d < 0 ? (d >> 1) : d));
                tma3d(dst, &v_map, row, bar);
                due += k < 12 ? T_V : T_V2;
                row += 16;
                bar += 8;
                dst = (k == 3) ? sb : dst + 8192;
            }
            if (proj) {
                due += T_GAP;
                mbar_wait(empty + 8 * 12);
                mbar_wait(empty + 8 * 13);
#pragma unroll 1
                for (int n = 0; n < 4; n++) {
                    mbar_expect_tx(bar, 8192);
                    if (gk != 7) mbar_wait(bar - 8 * MAX_O);
                    pace(due, bar - 8);
                    tma4d(sb + n * 8192, &wo_map, c * 64, (n + c) & 3, (2 * gk + (r >= 7)) * 2, bar);
                    due += T_O;
                    bar += 8;
                }
            }
            mbar_wait(done);
            if (spins >= SPIN_LIMIT) __trap();
        }
        return;
    }

    const int w = warp - 1, j = threadIdx.x - 32;
    const int g = lane >> 2, t = lane & 3;

    if (w < 7) {
        cluster_arrive();
        cluster_wait();
        const uint32_t qa = sb + (w * 32 + (lane >> 4) * 8 + (lane & 7)) * 128;
        const uint32_t xa = sb + OFF_OB + (g & 3) * 896 + (cta & 1) * 448 + w * 64 + t * 4;
        mbar_wait(qfull);
        const uint32_t x0 = lds32(xa), x1 = lds32(xa + 16), x2 = lds32(xa + 32), x3 = lds32(xa + 48);
        float cq[4][4];
#pragma unroll
        for (int m = 0; m < 4; m++) {
            const uint32_t a = qa + (((2 * m + ((lane >> 3) & 1)) ^ (lane & 7)) << 4);
            const uint4 f0 = ldsm4t(a), f1 = ldsm4t(a + 2048);
            cq[m][0] = cq[m][1] = cq[m][2] = cq[m][3] = 0.f;
            mma16816(cq[m], f0, x0, x1);
            mma16816(cq[m], f1, x2, x3);
        }
        slot_release(empty + 8 * (w >> 2), fu(cq[0][0]) ^ fu(cq[1][0]) ^ fu(cq[2][0]) ^ fu(cq[3][0]), zero, lane);
        const int hf = t >> 1;
        const uint32_t qr = sb + OFF_QRED + w * 1024 + (t & 1) * 512 + hf * 128 + g * 16;
        sts128f(qr, hf ? cq[0][2] : cq[0][0], hf ? cq[1][2] : cq[1][0], hf ? cq[2][2] : cq[2][0], hf ? cq[3][2] : cq[3][0]);
        sts128f(qr + 256, hf ? cq[0][3] : cq[0][1], hf ? cq[1][3] : cq[1][1], hf ? cq[2][3] : cq[2][1], hf ? cq[3][3] : cq[3][1]);
    } else {
        if (lane == 0) {
#pragma unroll
            for (int i = 0; i < 28; i++) mbar_init(kfull + 8 * i, 1);
#pragma unroll
            for (int i = 0; i < 14; i++) mbar_init(empty + 8 * i, i == 1 ? 3 : (i < 10 ? 4 : 8));
#pragma unroll
            for (int i = 0; i < 7; i++) mbar_init(qbar + 8 * i, 1);
            mbar_init(done, 8);
            mbar_expect_tx(qbar, 4096);
            mbar_expect_tx(stbar, 64);
            mbar_expect_tx(obar, 2048);
#pragma unroll
            for (int i = 0; i < 4; i++) mbar_expect_tx(hbar + 8 * i, 512);
            fence_mbar_init();
        }
        __syncwarp();
        cluster_arrive();
        cluster_wait();
    }
    bar_compute();
    {
        const int pk = j >> 2;
        const uint32_t ra = sb + OFF_QRED + pk * 16;
        float4 a = lds128f(ra);
#pragma unroll
        for (int ww = 1; ww < 7; ww++) {
            const float4 v = lds128f(ra + ww * 1024);
            a.x += v.x; a.y += v.y; a.z += v.z; a.w += v.w;
        }
        const uint32_t dst = (pk >> 4) * 4 + (j & 3);
        st_async128(mapa(sb + OFF_QBUF + (r & 1) * 2048 + (r >> 1) * 256 + (pk & 15) * 16, dst),
                    fu(a.x), fu(a.y), fu(a.z), fu(a.w), mapa(qbar, dst));
        mbar_wait(qbar);
        const uint32_t qb = sb + OFF_QBUF + (j >> 5) * 256 + (j & 7) * 32 + ((j >> 3) & 3) * 4;
        const float q0 = lds32f(qb) + lds32f(qb + 2048), q1 = lds32f(qb + 16) + lds32f(qb + 2064);
        sts32(sb + OFF_QS + ((j >> 5) & 3) * 256 + (j & 1) * 128 + (j >> 7) * 64 + ((j >> 2) & 3) * 16 + ((j >> 4) & 1) * 8 + ((j >> 1) & 1) * 4,
              pack_bf16(q0, q1));
    }
    bar_compute();

    float s0 = 0.f, s1 = 0.f;
    {
        uint2 qf[8];
        const uint32_t qa = sb + OFF_QS + (g >> 2) * 128 + (g & 1) * 64 + t * 16;
        const uint32_t qx = ((g >> 1) & 1) * 8;
#pragma unroll
        for (int i = 0; i < 8; i++) qf[i] = lds64(qa + (i >> 1) * 256 + (((i & 1) * 8) ^ qx));
        const uint32_t kx = (g & 1) * 64;
        const uint32_t krow = sb + ((w & 3) * 8 + g) * 512 + t * 16;
        const int src = (lane & 28) + (g & 1);
#pragma unroll 1
        for (int k = 0; k < 4; k++) {
            const int ch = 2 * k + (w >> 2);
            const uint32_t ka = krow + (ch >= 4 ? ch - 4 : ch + 2) * SLOT;
            mbar_wait(kfull + 8 * ch);
            float a0[4] = {0.f, 0.f, 0.f, 0.f}, a1[4] = {0.f, 0.f, 0.f, 0.f};
#pragma unroll
            for (int i = 0; i < 8; i += 2) {
                const uint4 r0 = lds128(ka + ((i * 64) ^ kx)), r1 = lds128(ka + (((i + 1) * 64) ^ kx));
                mma16816(a0, r0, qf[i].x, qf[i].y);
                mma16816(a1, r1, qf[i + 1].x, qf[i + 1].y);
            }
            const float e0 = __shfl_sync(0xffffffffu, a0[0] + a1[0], src) + __shfl_sync(0xffffffffu, a0[2] + a1[2], src + 2);
            const float e1 = __shfl_sync(0xffffffffu, a0[1] + a1[1], src) + __shfl_sync(0xffffffffu, a0[3] + a1[3], src + 2);
            slot_release(empty + 8 * (2 + ch), fu(e0), zero, lane);
            if (t == k) { s0 = e0; s1 = e1; }
        }
    }
    float Mown;
    {
        s0 = round_bf16(s0);
        s1 = round_bf16(s1);
        float m0 = s0, m1 = s1;
#pragma unroll
        for (int o = 16; o > 0; o >>= 1) {
            m0 = fmaxf(m0, __shfl_xor_sync(0xffffffffu, m0, o));
            m1 = fmaxf(m1, __shfl_xor_sync(0xffffffffu, m1, o));
        }
        if (lane < 2) sts32(sb + OFF_WST + (w * 2 + lane) * 4, fu(lane ? m1 : m0));
        bar_compute();
        const float4 u0 = lds128f(sb + OFF_WST), u1 = lds128f(sb + OFF_WST + 16), u2 = lds128f(sb + OFF_WST + 32), u3 = lds128f(sb + OFF_WST + 48);
        const float M0 = fmaxf(fmaxf(fmaxf(u0.x, u0.z), fmaxf(u1.x, u1.z)), fmaxf(fmaxf(u2.x, u2.z), fmaxf(u3.x, u3.z)));
        const float M1 = fmaxf(fmaxf(fmaxf(u0.y, u0.w), fmaxf(u1.y, u1.w)), fmaxf(fmaxf(u2.y, u2.w), fmaxf(u3.y, u3.w)));
        Mown = (t & 1) ? M1 : M0;
        const uint32_t p = pack_bf16(exp_score(s0 - M0), exp_score(s1 - M1));
        const uint32_t pa = sb + OFF_PS + (4 * t + (w >> 1)) * 64 + (g >> 1) * 8 + (w & 1) * 4 + (g & 1) * 2;
        sts16(pa, (unsigned short)(p & 0xFFFFu));
        sts16(pa + 32, (unsigned short)(p >> 16));
        float l0 = __uint_as_float(p << 16), l1 = __uint_as_float(p & 0xFFFF0000u);
#pragma unroll
        for (int o = 16; o > 0; o >>= 1) {
            l0 += __shfl_xor_sync(0xffffffffu, l0, o);
            l1 += __shfl_xor_sync(0xffffffffu, l1, o);
        }
        if (lane < 2) sts32(sb + OFF_WST + 64 + (w * 2 + lane) * 4, fu(lane ? l1 : l0));
        bar_compute();
        if (j < 4) {
            const float4 v0 = lds128f(sb + OFF_WST + 64), v1 = lds128f(sb + OFF_WST + 80), v2 = lds128f(sb + OFF_WST + 96), v3 = lds128f(sb + OFF_WST + 112);
            const float L0 = ((v0.x + v0.z) + (v1.x + v1.z)) + ((v2.x + v2.z) + (v3.x + v3.z));
            const float L1 = ((v0.y + v0.w) + (v1.y + v1.w)) + ((v2.y + v2.w) + (v3.y + v3.w));
            st_async128(mapa(sb + OFF_WST + 128 + s * 16, b * 4 + j), fu(M0), fu(L0), fu(M1), fu(L1), mapa(stbar, b * 4 + j));
        }
    }

    const uint32_t h1_dst = pin(mapa(sb + OFF_HOP + r * 128 + (t >> 1) * 64 + g * 8, (t & 1) * 8 + w));
    const uint32_t h1_bar = pin(mapa(hbar + 8 * b, (t & 1) * 8 + w));
    const uint32_t h2_grp = (w >> 2) * 4 + (lane >> 3);
    const uint32_t h2_rank = h2_grp < 7 ? (r >> 3) * 7 + h2_grp : 14 + (r >> 3);
    const uint32_t h2_dst = pin(mapa(sb + OFF_OB + (w & 3) * OB_STRIDE + ((r - h2_grp) & 3) * 128 + ((r >> 2) & 1) * 64 +
                                     (lane & 3) * 16 + ((lane >> 2) & 1) * 8, h2_rank));
    const uint32_t h2_bar = pin(mapa(obar, h2_rank));
    const uint32_t h2_src = pin(sb + OFF_HOP + (w & 3) * 512 + (lane & 7) * 16);
    const uint32_t h2_wait = pin(hbar + 8 * (w & 3));
    const uint32_t bars = pin(obar);
    const uint32_t wo_src = pin(sb + (((lane >> 3) & 1) * 16 + (lane >> 4) * 8 + (lane & 7)) * 128 + ((w ^ (lane & 7)) << 4));
    const uint32_t ob_src = pin(sb + OFF_OB + (g & 3) * OB_STRIDE + (g >> 2) * 64 + t * 16);
    unsigned long long* acc_p = pin_ptr(acc + (c & 3) * 2048 + 512 + (c >> 2) * 512 + (j >> 4) * 32 + (j & 15));
    __nv_bfloat16* out_p = pin_ptr(out + (g & 3) * 448 + c * 64 + w * 8 + 2 * t + (g >> 2));
    const uint32_t k_one = pin(zero + 1u);
    const bool t_hi = pin(t >> 1) != 0, g_hi = pin(g >> 2) != 0, proj_on = pin(proj ? 1u : 0u) != 0;

    float acc0[4] = {0.f, 0.f, 0.f, 0.f}, acc1[4] = {0.f, 0.f, 0.f, 0.f};
    float wgt;
    {
        const uint32_t va0 = pin(sb + (w >> 1) * 2048 + ((lane >> 4) * 8 + (lane & 7)) * 128 + ((((w & 1) * 4 + ((lane >> 3) & 1)) ^ (lane & 7)) << 4));
        const uint32_t va1 = pin(va0 ^ 32);
        const uint32_t pa = pin(sb + OFF_PS + ((g >> 1) & 1) * 32 + t * 8);
        const uint32_t vb = bars - (obar - vfull);
#pragma unroll 1
        for (int k = 0; k < 8; k += 2) {
            const uint32_t so = (k < 4 ? k + 8 : k - 4) * 8192;
            const uint2 p0 = lds64(pa + k * 64), p1 = lds64(pa + k * 64 + 64);
            mbar_wait(vb + 8 * k);
            const uint4 f0 = ldsm4t(va0 + so), f1 = ldsm4t(va1 + so);
            mma16816(acc0, f0, p0.x, p0.y);
            mma16816(acc1, f1, p0.x, p0.y);
            mbar_wait(vb + 8 * k + 8);
            const uint4 f2 = ldsm4t(va0 + so + 8192), f3 = ldsm4t(va1 + so + 8192);
            mma16816(acc0, f2, p1.x, p1.y);
            mma16816(acc1, f3, p1.x, p1.y);
            slot_release(empty + 8 * (10 + (k >> 1)), fu(acc0[0]) ^ fu(acc1[0]), zero, lane);
        }
        uint2 pw[8];
#pragma unroll
        for (int k = 8; k < 16; k++) pw[k - 8] = lds64(pa + k * 64);
        {
            mbar_wait(stbar);
            const uint32_t sa = sb + OFF_WST + 128 + (t & 1) * 8;
            const float2 z0 = lds64f(sa), z1 = lds64f(sa + 16), z2 = lds64f(sa + 32), z3 = lds64f(sa + 48);
            const float mx = fmaxf(fmaxf(z0.x, z1.x), fmaxf(z2.x, z3.x));
            const float W = (exp_score(z0.x - mx) * z0.y + exp_score(z1.x - mx) * z1.y) +
                            (exp_score(z2.x - mx) * z2.y + exp_score(z3.x - mx) * z3.y);
            wgt = __uint_as_float(pin(fu(__fdividef(exp_score(Mown - mx), W))));
        }
        uint4 f0, f1;
#pragma unroll
        for (int k = 8; k < 16; k++) {
            mbar_wait_fast(vb + 8 * k);
            const uint4 n0 = ldsm4t(va0 + (k - 4) * 8192), n1 = ldsm4t(va1 + (k - 4) * 8192);
            if (k > 8) {
                mma16816(acc0, f0, pw[k - 9].x, pw[k - 9].y);
                mma16816(acc1, f1, pw[k - 9].x, pw[k - 9].y);
            }
            f0 = n0; f1 = n1;
        }
        mma16816(acc0, f0, pw[7].x, pw[7].y);
        mma16816(acc1, f1, pw[7].x, pw[7].y);
    }
    st_async64(h1_dst, fu((t_hi ? acc1[0] : acc0[0]) * wgt), fu((t_hi ? acc1[2] : acc0[2]) * wgt), h1_bar);
    {
        mbar_wait_fast(h2_wait);
        const float4 v0 = lds128f(h2_src), v1 = lds128f(h2_src + 128), v2 = lds128f(h2_src + 256), v3 = lds128f(h2_src + 384);
        st_async64(h2_dst, pack_bf16((v0.x + v1.x) + (v2.x + v3.x), (v0.z + v1.z) + (v2.z + v3.z)),
                   pack_bf16((v0.y + v1.y) + (v2.y + v3.y), (v0.w + v1.w) + (v2.w + v3.w)), h2_bar);
    }
    if (!proj_on) {
        mbar_wait_fast(bars);
        slot_release(bars + (done - obar), 0u, 0u, lane);
        return;
    }
    float sum;
    {
        const uint32_t ob = bars - (obar - ofull);
        float x0[4] = {0.f, 0.f, 0.f, 0.f}, x1[4] = {0.f, 0.f, 0.f, 0.f}, y0[4] = {0.f, 0.f, 0.f, 0.f}, y1[4] = {0.f, 0.f, 0.f, 0.f};
        uint4 bp[4], bq[4], oa[4];
#pragma unroll
        for (int n = 0; n < 4; n++) {
            mbar_wait_fast(ob + 8 * n);
            bp[n] = ldsm4t(wo_src + n * 8192);
            bq[n] = ldsm4t(wo_src + n * 8192 + 4096);
            if (n == 0) continue;
            if (n == 1) {
                mbar_wait_fast(bars);
#pragma unroll
                for (int i = 0; i < 4; i++) oa[i] = lds128(ob_src + i * 128);
            }
#pragma unroll
            for (int i = (n == 1 ? 0 : n); i <= n; i++) {
                mma16816(x0, oa[i], bp[i].x, bp[i].y);
                mma16816(y0, oa[i], bp[i].z, bp[i].w);
                mma16816(x1, oa[i], bq[i].x, bq[i].y);
                mma16816(y1, oa[i], bq[i].z, bq[i].w);
            }
        }
        float keep = x0[0] + y0[2], send = x0[1] + y0[3];
        if (g_hi) { send = x1[0] + y1[2]; keep = x1[1] + y1[3]; }
        sum = keep + __shfl_xor_sync(0xffffffffu, send, 16);
    }
    const uint32_t bits = fu(sum);
    const uint32_t sh = 129u - ((bits >> 23) & 0xFFu);
    const uint32_t smant = (((bits << 3) & 0x3FFFFF8u) | 0x4000000u) ^ (uint32_t)((int)bits >> 31);
    long long fx;
    asm("shr.s64 %0, %1, %2;" : "=l"(fx) : "l"((long long)((unsigned long long)smant << 32)), "r"(sh));
    const unsigned long long inc = ((unsigned long long)fx & 0xFFFFFFFF00000000ull) | (((uint32_t)fx & ~0x3FFu) | k_one);
    const bool fast = __any_sync(0xffffffffu, fabsf(sum) >= 0x1p-22f) && fabsf(sum) < 8.0f;
    unsigned long long tot = 0ull;
    asm volatile("{\n.reg .pred p;\nsetp.ne.u32 p, %3, 0;\n@p atom.relaxed.gpu.global.add.u64 %0, [%1], %2;\n}"
                 : "+l"(tot) : "l"(acc_p), "l"(inc), "r"((uint32_t)fast) : "memory");
    slot_release(bars + (done - obar), 0u, 0u, lane);
    if (!fast) { accumulate_slow(sum, acc_p, out_p); return; }
    tot += inc;
    const uint32_t cnt = (uint32_t)tot & 0x3FFu;
    asm volatile("{\n.reg .pred p;\nsetp.eq.u32 p, %3, 16;\n@p st.global.u16 [%0], %1;\n@p st.global.u64 [%2], 0;\n}"
                 ::"l"(out_p), "h"(__bfloat16_as_ushort(__float2bfloat16(acc_value(tot)))), "l"(acc_p), "r"(cnt) : "memory");
    if (cnt > 16u) finish_with_side(tot, acc_p, out_p);
}

typedef CUresult (*EncodeFn)(CUtensorMap*, CUtensorMapDataType, cuuint32_t, void*, const cuuint64_t*, const cuuint64_t*,
                             const cuuint32_t*, const cuuint32_t*, CUtensorMapInterleave, CUtensorMapSwizzle,
                             CUtensorMapL2promotion, CUtensorMapFloatOOBfill);

}

extern "C" void kernel_launch(void* const* d_in, const int* in_sizes, int n_in, void* d_out, int out_size) {
    (void)in_sizes; (void)n_in; (void)out_size;
    static EncodeFn encode = nullptr;
    static void* acc = nullptr;
    if (!encode) {
        cudaDriverEntryPointQueryResult qr;
        cudaGetDriverEntryPoint("cuTensorMapEncodeTiled", (void**)&encode, cudaEnableDefault, &qr);
        cudaGetSymbolAddress(&acc, g_acc);
        cudaFuncSetAttribute(decode_kernel, cudaFuncAttributeMaxDynamicSharedMemorySize, SMEM_BYTES);
        cudaFuncSetAttribute(decode_kernel, cudaFuncAttributeNonPortableClusterSizeAllowed, 1);
    }
    const cuuint32_t estr[4] = {1, 1, 1, 1};
    CUtensorMap wq_map, wo_map, v_map;
    {
        const cuuint64_t dim[2] = {4096, 448}, str[1] = {8192};
        const cuuint32_t box[2] = {64, 224};
        encode(&wq_map, CU_TENSOR_MAP_DATA_TYPE_BFLOAT16, 2, d_in[3], dim, str, box, estr, CU_TENSOR_MAP_INTERLEAVE_NONE,
               CU_TENSOR_MAP_SWIZZLE_128B, CU_TENSOR_MAP_L2_PROMOTION_NONE, CU_TENSOR_MAP_FLOAT_OOB_FILL_NONE);
    }
    {
        const cuuint64_t dim[4] = {448, 32, 4, 32}, str[3] = {896, 896 * 32, 896 * 128};
        const cuuint32_t box[4] = {64, 32, 1, 2};
        encode(&wo_map, CU_TENSOR_MAP_DATA_TYPE_BFLOAT16, 4, d_in[4], dim, str, box, estr, CU_TENSOR_MAP_INTERLEAVE_NONE,
               CU_TENSOR_MAP_SWIZZLE_128B, CU_TENSOR_MAP_L2_PROMOTION_NONE, CU_TENSOR_MAP_FLOAT_OOB_FILL_NONE);
    }
    {
        const cuuint64_t dim[3] = {64, 4ull * 8 * SK, 4}, str[2] = {512, 128};
        const cuuint32_t box[3] = {64, 16, 4};
        encode(&v_map, CU_TENSOR_MAP_DATA_TYPE_BFLOAT16, 3, d_in[2], dim, str, box, estr, CU_TENSOR_MAP_INTERLEAVE_NONE,
               CU_TENSOR_MAP_SWIZZLE_128B, CU_TENSOR_MAP_L2_PROMOTION_NONE, CU_TENSOR_MAP_FLOAT_OOB_FILL_NONE);
    }
    cudaLaunchConfig_t cfg = {};
    cfg.gridDim = dim3(128);
    cfg.blockDim = dim3(NTHREADS);
    cfg.dynamicSmemBytes = SMEM_BYTES;
    cfg.stream = cudaStreamPerThread;
    cudaLaunchAttribute attr[2];
    attr[0].id = cudaLaunchAttributeClusterDimension;
    attr[0].val.clusterDim.x = 16; attr[0].val.clusterDim.y = 1; attr[0].val.clusterDim.z = 1;
    attr[1].id = cudaLaunchAttributeClusterSchedulingPolicyPreference;
    attr[1].val.clusterSchedulingPolicyPreference = cudaClusterSchedulingPolicyLoadBalancing;
    cfg.attrs = attr;
    cfg.numAttrs = 2;
    cudaLaunchKernelEx(&cfg, decode_kernel, (const __nv_bfloat16*)d_in[0], (const __nv_bfloat16*)d_in[1],
                       (const __nv_bfloat16*)d_in[3], (__nv_bfloat16*)d_out, (unsigned long long*)acc, 0u,
                       wq_map, wo_map, v_map);
}
```
